```python
import torch

def _softmax(x, axis=-1):
    return torch.softmax(x, dim=axis)
def _gelu(x):
    return torch.nn.functional.gelu(x, approximate="tanh")
def _silu(x):
    return torch.nn.functional.silu(x)
def _sigmoid(x):
    return torch.sigmoid(x)
def _layernorm(x, axis=-1, eps=1e-5):
    m = x.mean(dim=axis, keepdim=True)
    v = x.var(dim=axis, keepdim=True, unbiased=False)
    return (x - m) / torch.sqrt(v + eps)
def _scatter_add(tgt, idx, src, axis=0):
    return tgt.clone().index_add_(axis, idx, src)
def _segment_sum(src, seg, n):
    out = torch.zeros((n,) + src.shape[1:], dtype=src.dtype)
    return out.index_add_(0, seg, src)
def _pad(x, pw):
    flat = tuple(v for pair in reversed(pw) for v in pair)
    return torch.nn.functional.pad(x, flat)

kernel_name = 'sequential_preLN__sliding_block__dense_activation_squared_relu__prompt'

def setup_inputs():

    _w = (lambda a: (lambda t: t.to(torch.bfloat16) if t.is_floating_point() else t)(torch.as_tensor(a)))
    def _A_setup():
        B, S, D = 1, 2048, 640
        return {
            "x": _w((lambda *s: torch.randn(*s, dtype=torch.bfloat16) * 0.05)(B, S, D)),
            "wqkv": _w((lambda *s: torch.randn(*s, dtype=torch.bfloat16) * 0.05)(D, 3 * D)),
            "wo": _w((lambda *s: torch.randn(*s, dtype=torch.bfloat16) * 0.05)(D, D)),
        }
    _A_in = _A_setup()

    def _B_setup():
        B, S, D, F = 1, 2048, 640, 1536
        return {
            "x": _w((lambda *s: torch.randn(*s, dtype=torch.bfloat16) * 0.05)(B, S, D)),
            "w1": _w((lambda *s: torch.randn(*s, dtype=torch.bfloat16) * 0.05)(D, F)),
            "b1": _w((lambda *s: torch.randn(*s, dtype=torch.bfloat16) * 0.4)(F)),
            "w2": _w((lambda *s: torch.randn(*s, dtype=torch.bfloat16) * 0.05)(F, D)),
            "b2": _w((lambda *s: torch.randn(*s, dtype=torch.bfloat16) * 3.2)(D)),
        }
    _B_in = _B_setup()

    return {
        "A_x": _A_in["x"],
        "A_wqkv": _A_in["wqkv"],
        "A_wo": _A_in["wo"],
        "B_x": _B_in["x"],
        "B_w1": _B_in["w1"],
        "B_b1": _B_in["b1"],
        "B_w2": _B_in["w2"],
        "B_b2": _B_in["b2"],
    }

def reference(A_x, A_wqkv, A_wo, B_x, B_w1, B_b1, B_w2, B_b2):
    def _A_ref(x, wqkv, wo):
        B, S, D = x.shape
        H = 32; Dh = D // H; W = 256
        qkv = (lambda x, *d: x.permute(*d))((x @ wqkv).reshape(B, S, 3, H, Dh), 2, 0, 3, 1, 4)
        q, k, v = qkv[0], qkv[1], qkv[2]
        scores = torch.einsum("bhqd,bhkd->bhqk", q, k) * (Dh ** -0.5)
        idx = torch.arange(S)
        mask = (idx[:, None] - idx[None, :] >= 0) & (idx[:, None] - idx[None, :] < W)
        scores = torch.where(mask[None, None], scores, -1e9)
        p = _softmax(scores, axis=-1)
        o = torch.einsum("bhqk,bhkd->bhqd", p, v)
        return (lambda x, *d: x.permute(*d))(o, 0, 2, 1, 3).reshape(B, S, D) @ wo

    def _B_ref(x, w1, b1, w2, b2):
        h = torch.einsum("bsd,df->bsf", x, w1) + b1
        zero = torch.zeros_like(h)
        r = torch.where(h > zero, h, zero)
        h = r * r
        out = torch.einsum("bsf,fd->bsd", h, w2) + b2
        return out

    x = A_x
    h = x + _A_ref(_layernorm(x, axis=-1), A_wqkv, A_wo)
    h2 = h + _B_ref(_layernorm(h, axis=-1), B_w1, B_b1, B_w2, B_b2)
    return h2
```

```cpp
#include <cuda_runtime.h>
#include <cuda.h>
#include <cuda_bf16.h>
#include <stdint.h>

namespace blk {

constexpr int SEQ = 2048, DM = 640, FF = 1536;
constexpr int NCTA = 128;

constexpr uint32_t A_STAGE = 47104;
constexpr uint32_t CS_STG0 = 188416, CS_STG1 = 217088;
constexpr uint32_t KV_BLK = 45056;
constexpr uint32_t KV_FAR = 0, KV_PREV = 45056, KV_OWN = 90112;
constexpr uint32_t WO_OFF = 135168, WO4_OFF = 102400;
constexpr uint32_t OT_BYTES = 20480;
constexpr uint32_t HT_BYTES = 21504;
constexpr uint32_t DB_OFF = 98304, DB_SLOT = 30720;
constexpr uint32_t EB_OFF = 98304, EB_SLOT = 24576;
constexpr uint32_t AUX = 225280;
constexpr uint32_t BARS = AUX;
constexpr uint32_t S_CS1 = AUX + 512;
constexpr uint32_t S_CS2 = AUX + 1536;
constexpr uint32_t S_EPOCH = AUX + 3072;
constexpr uint32_t SMEM_BYTES = AUX + 3072 + 64;

enum Bar : int {
  B_AFULL = 0, B_AEMPTY = 4, B_STAT = 8, B_KVW = 9, B_KVFULL = 10  , B_KVST = 12, B_AUXDONE = 13, B_WOFULL = 14,
  B_ATTDONE = 15, B_CFULL = 16  , B_WO4 = 21, B_CEMPTY = 22  , B_CDONE = 25, B_HW = 26, B_DAFULL = 27  , B_DAEMPTY = 31  ,
  B_DBFULL = 35  , B_DBEMPTY = 39  , B_DDONE = 43, B_FW = 44, B_FFULL = 45  , B_EBFULL = 48  , B_EBEMPTY = 53  ,
  B_CS2 = 58, B_EPOCH = 59, B_AUX2 = 60, B_COUNT = 61
};
constexpr int bar_count(int i) {
  return i < 4 ? 2 : i < 8 ? 4 : i == B_KVW || i == B_HW || i == B_FW ? 8 : i == B_ATTDONE || i == B_CDONE || i == B_DDONE ? 4
       : i >= B_CEMPTY && i < B_CEMPTY + 3 ? 4 : i == B_DAEMPTY ? 6 : i > B_DAEMPTY && i < B_DAEMPTY + 4 ? 4
       : i >= B_DBEMPTY && i < B_DBEMPTY + 4 ? 2 : i >= B_EBEMPTY && i < B_EBEMPTY + 5 ? 2 : 1;
}
constexpr unsigned long long bar_pack(int w) {
  unsigned long long v = 0;
  for (int i = 0; i < 16; i++) v |= (unsigned long long)bar_count(w * 16 + i) << (4 * i);
  return v;
}
constexpr unsigned long long BAR_PK0 = bar_pack(0), BAR_PK1 = bar_pack(1), BAR_PK2 = bar_pack(2), BAR_PK3 = bar_pack(3);

__device__ __align__(1024) uint4 g_kv[128 * (KV_BLK / 16)];
__device__ __align__(1024) uint4 g_o[128 * (OT_BYTES / 16)];
__device__ __align__(1024) uint4 g_h[128 * (HT_BYTES / 16)];
__device__ __align__(1024) uint4 g_part[16 * 2 * 4 * 4 * 8 * 5 * 32];
__device__ __align__(128) unsigned long long g_cs[3 * DM + FF];
constexpr int FL_EPOCH = 0, FL_KV = 128, FL_O = 256, FL_H = 384, FL_P = 512;
__device__ __align__(1024) unsigned g_flags[512 + 16 * 2 * 2 * 8 * 4];
#define PROF_T(i) do {} while (0)

__device__ __forceinline__ uint32_t smem_u32(const void* p) { return (uint32_t)__cvta_generic_to_shared(p); }
__device__ __forceinline__ void mbar_init(uint32_t bar, uint32_t cnt) { asm volatile("mbarrier.init.shared::cta.b64 [%0], %1;" :: "r"(bar), "r"(cnt)); }
__device__ __forceinline__ void mbar_expect_tx(uint32_t bar, uint32_t bytes) { asm volatile("mbarrier.arrive.expect_tx.shared::cta.b64 _, [%0], %1;" :: "r"(bar), "r"(bytes) : "memory"); }
__device__ __forceinline__ void mbar_arrive(uint32_t bar) { asm volatile("mbarrier.arrive.shared::cta.b64 _, [%0];" :: "r"(bar) : "memory"); }
__device__ __forceinline__ uint32_t mapa(uint32_t addr, uint32_t cta) { uint32_t r; asm volatile("mapa.shared::cluster.u32 %0, %1, %2;" : "=r"(r) : "r"(addr), "r"(cta)); return r; }
__device__ __forceinline__ void mbar_arrive_cluster(uint32_t bar, uint32_t cta) {
  asm volatile("{\n.reg .b32 ra;\nmapa.shared::cluster.u32 ra, %0, %1;\nmbarrier.arrive.shared::cluster.b64 _, [ra];\n}" :: "r"(bar), "r"(cta) : "memory");
}
constexpr unsigned SPIN_LIMIT = 4000000u;
__device__ __forceinline__ void spin_guard(unsigned& n) { asm volatile("{\n.reg .pred p;\nadd.u32 %0, %0, 1;\nsetp.gt.u32 p, %0, %1;\n@p trap;\n}" : "+r"(n) : "n"(SPIN_LIMIT)); }
__device__ __forceinline__ void mbar_wait(uint32_t bar, uint32_t parity) {
  asm volatile("{\n.reg .pred p;\n.reg .u32 n;\nmov.u32 n, 0;\nWAIT_%=:\nmbarrier.try_wait.parity.shared::cta.b64 p, [%0], %1;\n@p bra DONE_%=;\n"
               "add.u32 n, n, 1;\nsetp.gt.u32 p, n, 0x4000000;\n@p trap;\nbra WAIT_%=;\nDONE_%=:\n}" :: "r"(bar), "r"(parity) : "memory");
}
__device__ __forceinline__ unsigned ld_relaxed(const unsigned* p) { unsigned v; asm volatile("ld.relaxed.gpu.global.u32 %0, [%1];" : "=r"(v) : "l"(p) : "memory"); return v; }
__device__ __forceinline__ unsigned long long ld_relaxed64(const unsigned long long* p) { unsigned long long v; asm volatile("ld.relaxed.gpu.global.u64 %0, [%1];" : "=l"(v) : "l"(p) : "memory"); return v; }
__device__ __forceinline__ void st_relaxed(unsigned* p, unsigned v) { asm volatile("st.relaxed.gpu.global.u32 [%0], %1;" :: "l"(p), "r"(v) : "memory"); }
__device__ __forceinline__ void st_relaxed64(unsigned long long* p, unsigned lo, unsigned hi) {
  asm volatile("{\n.reg .b64 v;\nmov.b64 v, {%1, %2};\nst.relaxed.gpu.global.u64 [%0], v;\n}" :: "l"(p), "r"(lo), "r"(hi) : "memory");
}
__device__ __forceinline__ void st_release(unsigned* p, unsigned v) { asm volatile("st.release.gpu.global.u32 [%0], %1;" :: "l"(p), "r"(v) : "memory"); }
__device__ __forceinline__ void red_release(unsigned* p, unsigned v) { asm volatile("red.release.gpu.global.add.u32 [%0], %1;" :: "l"(p), "r"(v) : "memory"); }
__device__ __forceinline__ void fence_acq() { asm volatile("fence.acq_rel.gpu;" ::: "memory"); }
__device__ __forceinline__ void fence_async() { asm volatile("fence.proxy.async.shared::cta;" ::: "memory"); }
__device__ __forceinline__ void fence_async_all() { asm volatile("fence.proxy.async;" ::: "memory"); }
__device__ __forceinline__ void wait_flag(const unsigned* p, unsigned target) {
  unsigned n = 0;
  while ((int)(ld_relaxed(p) - target) < 0) spin_guard(n);
}
__device__ __forceinline__ void tma_2d(uint32_t dst, const CUtensorMap* map, int c0, int c1, uint32_t bar) {
  asm volatile("cp.async.bulk.tensor.2d.shared::cluster.global.mbarrier::complete_tx::bytes [%0], [%1, {%3, %4}], [%2];"
    :: "r"(dst), "l"(map), "r"(bar), "r"(c0), "r"(c1) : "memory");
}
__device__ __forceinline__ void tma_3d(uint32_t dst, const CUtensorMap* map, int c0, int c1, int c2, uint32_t bar) {
  asm volatile("cp.async.bulk.tensor.3d.shared::cluster.global.mbarrier::complete_tx::bytes [%0], [%1, {%3, %4, %5}], [%2];"
    :: "r"(dst), "l"(map), "r"(bar), "r"(c0), "r"(c1), "r"(c2) : "memory");
}
__device__ __forceinline__ void tma_3d_mc(uint32_t dst, const CUtensorMap* map, int c0, int c1, int c2, uint32_t bar) {
  asm volatile("cp.async.bulk.tensor.3d.shared::cluster.global.mbarrier::complete_tx::bytes.multicast::cluster [%0], [%1, {%3, %4, %5}], [%2], %6;"
    :: "r"(dst), "l"(map), "r"(bar), "r"(c0), "r"(c1), "r"(c2), "h"((uint16_t)3) : "memory");
}
__device__ __forceinline__ void bulk_ld(uint32_t dst, const void* src, uint32_t bytes, uint32_t bar) {
  asm volatile("cp.async.bulk.shared::cluster.global.mbarrier::complete_tx::bytes [%0], [%1], %2, [%3];" :: "r"(dst), "l"(src), "r"(bytes), "r"(bar) : "memory");
}
__device__ __forceinline__ void bulk_ld_mc(uint32_t dst, const void* src, uint32_t bytes, uint32_t bar) {
  asm volatile("cp.async.bulk.shared::cluster.global.mbarrier::complete_tx::bytes.multicast::cluster [%0], [%1], %2, [%3], %4;"
    :: "r"(dst), "l"(src), "r"(bytes), "r"(bar), "h"((uint16_t)3) : "memory");
}
__device__ __forceinline__ void bulk_st(void* dst, uint32_t src, uint32_t bytes) {
  asm volatile("cp.async.bulk.global.shared::cta.bulk_group [%0], [%1], %2;" :: "l"(dst), "r"(src), "r"(bytes) : "memory");
}
__device__ __forceinline__ void bulk_dsmem(uint32_t rdst, uint32_t src, uint32_t bytes, uint32_t rbar) {
  asm volatile("cp.async.bulk.shared::cluster.shared::cta.mbarrier::complete_tx::bytes [%0], [%1], %2, [%3];" :: "r"(rdst), "r"(src), "r"(bytes), "r"(rbar) : "memory");
}
__device__ __forceinline__ void bulk_commit() { asm volatile("cp.async.bulk.commit_group;" ::: "memory"); }
__device__ __forceinline__ void bulk_wait0() { asm volatile("cp.async.bulk.wait_group 0;" ::: "memory"); }
__device__ __forceinline__ void prefetch_l2(const void* p, uint32_t bytes) { asm volatile("cp.async.bulk.prefetch.L2.global [%0], %1;" :: "l"(p), "r"(bytes) : "memory"); }
__device__ __forceinline__ void prefetch_map(const CUtensorMap* m) { asm volatile("prefetch.tensormap [%0];" :: "l"(m) : "memory"); }
__device__ __forceinline__ void cp_async16(uint32_t dst, const void* src) { asm volatile("cp.async.cg.shared.global [%0], [%1], 16;" :: "r"(dst), "l"(src) : "memory"); }
__device__ __forceinline__ void cp_async_wait_all() { asm volatile("cp.async.wait_all;" ::: "memory"); }
__device__ __forceinline__ void cluster_arrive() { asm volatile("barrier.cluster.arrive.release.aligned;" ::: "memory"); }
__device__ __forceinline__ void cluster_wait() { asm volatile("barrier.cluster.wait.acquire.aligned;" ::: "memory"); }
__device__ __forceinline__ void named_sync(int id, int n) { asm volatile("bar.sync %0, %1;" :: "r"(id), "r"(n) : "memory"); }
__device__ __forceinline__ void wg_fence() { asm volatile("wgmma.fence.sync.aligned;" ::: "memory"); }
__device__ __forceinline__ void wg_commit() { asm volatile("wgmma.commit_group.sync.aligned;" ::: "memory"); }
template <int N> __device__ __forceinline__ void wg_wait() { asm volatile("wgmma.wait_group.sync.aligned %0;" :: "n"(N) : "memory"); }
template <int N> __device__ __forceinline__ void reg_fence(float (&d)[N]) {
  #pragma unroll
  for (int i = 0; i < N; i++) asm volatile("" : "+f"(d[i]) :: "memory");
}
__device__ __forceinline__ uint64_t make_desc(uint32_t addr, uint32_t lbo, uint32_t sbo, uint32_t swz) {
  return (uint64_t)((addr & 0x3FFFF) >> 4) | ((uint64_t)(lbo >> 4) << 16) | ((uint64_t)(sbo >> 4) << 32) | ((uint64_t)swz << 62);
}
__device__ __forceinline__ uint32_t pack2(float lo, float hi) { uint32_t r; asm("cvt.rn.bf16x2.f32 %0, %1, %2;" : "=r"(r) : "f"(hi), "f"(lo)); return r; }
__device__ __forceinline__ uint32_t pack2_relu(float lo, float hi) { uint32_t r; asm("cvt.rn.relu.bf16x2.f32 %0, %1, %2;" : "=r"(r) : "f"(hi), "f"(lo)); return r; }
__device__ __forceinline__ uint32_t sq2(uint32_t v) { uint32_t r; asm("mul.rn.bf16x2 %0, %1, %1;" : "=r"(r) : "r"(v)); return r; }
__device__ __forceinline__ float bf_lo(uint32_t v) { return __uint_as_float(v << 16); }
__device__ __forceinline__ float bf_hi(uint32_t v) { return __uint_as_float(v & 0xffff0000u); }
__device__ __forceinline__ float ex2(float x) { float r; asm("ex2.approx.ftz.f32 %0, %1;" : "=f"(r) : "f"(x)); return r; }
__device__ __forceinline__ float rcp(float x) { float r; asm("rcp.approx.ftz.f32 %0, %1;" : "=f"(r) : "f"(x)); return r; }
__device__ __forceinline__ float rsq(float x) { float r; asm("rsqrt.approx.ftz.f32 %0, %1;" : "=f"(r) : "f"(x)); return r; }
__device__ __forceinline__ void stsm4(uint32_t addr, uint32_t a, uint32_t b, uint32_t c, uint32_t d) {
  asm volatile("stmatrix.sync.aligned.m8n8.x4.shared.b16 [%0], {%1, %2, %3, %4};" :: "r"(addr), "r"(a), "r"(b), "r"(c), "r"(d) : "memory");
}
__device__ __forceinline__ void ldsm4(uint32_t addr, uint32_t (&r)[4]) {
  asm volatile("ldmatrix.sync.aligned.m8n8.x4.shared.b16 {%0, %1, %2, %3}, [%4];" : "=r"(r[0]), "=r"(r[1]), "=r"(r[2]), "=r"(r[3]) : "r"(addr) : "memory");
}
__device__ __forceinline__ float2 lds_f2(uint32_t a) { float2 v; asm volatile("ld.shared.v2.f32 {%0, %1}, [%2];" : "=f"(v.x), "=f"(v.y) : "r"(a)); return v; }
__device__ __forceinline__ float4 lds_f4(uint32_t a) { float4 v; asm volatile("ld.shared.v4.f32 {%0, %1, %2, %3}, [%4];" : "=f"(v.x), "=f"(v.y), "=f"(v.z), "=f"(v.w) : "r"(a)); return v; }
__device__ __forceinline__ uint4 lds_u4(uint32_t a) { uint4 v; asm volatile("ld.shared.v4.u32 {%0, %1, %2, %3}, [%4];" : "=r"(v.x), "=r"(v.y), "=r"(v.z), "=r"(v.w) : "r"(a)); return v; }
__device__ __forceinline__ void sts_f2(uint32_t a, float x, float y) { asm volatile("st.shared.v2.f32 [%0], {%1, %2};" :: "r"(a), "f"(x), "f"(y) : "memory"); }
__device__ __forceinline__ void sts_u32(uint32_t a, uint32_t x) { asm volatile("st.shared.u32 [%0], %1;" :: "r"(a), "r"(x) : "memory"); }
__device__ __forceinline__ uint32_t lds_u32(uint32_t a) { uint32_t v; asm volatile("ld.shared.u32 %0, [%1];" : "=r"(v) : "r"(a) : "memory"); return v; }
__device__ __forceinline__ uint32_t ldg_u32(const void* p) { uint32_t v; asm volatile("ld.global.nc.u32 %0, [%1];" : "=r"(v) : "l"(p)); return v; }
__device__ __forceinline__ uint4 ldg_cg_u4(const void* p) { uint4 v; asm volatile("ld.global.cg.v4.u32 {%0, %1, %2, %3}, [%4];" : "=r"(v.x), "=r"(v.y), "=r"(v.z), "=r"(v.w) : "l"(p) : "memory"); return v; }
__device__ __forceinline__ float quad_max(float v) { v = fmaxf(v, __shfl_xor_sync(~0u, v, 1)); return fmaxf(v, __shfl_xor_sync(~0u, v, 2)); }
__device__ __forceinline__ float quad_sum(float v) { v += __shfl_xor_sync(~0u, v, 1); return v + __shfl_xor_sync(~0u, v, 2); }

__device__ __forceinline__ void wgmma_rs_n192_t1(float (&d)[96], uint32_t a0, uint32_t a1, uint32_t a2, uint32_t a3, uint64_t db, int scale_d) {
  asm volatile("{\n.reg .pred p;\nsetp.ne.b32 p, %101, 0;\nwgmma.mma_async.sync.aligned.m64n192k16.f32.bf16.bf16 {%0, %1, %2, %3, %4, %5, %6, %7, %8, %9, %10, %11, %12, %13, %14, %15, %16, %17, %18, %19, %20, %21, %22, %23, %24, %25, %26, %27, %28, %29, %30, %31, %32, %33, %34, %35, %36, %37, %38, %39, %40, %41, %42, %43, %44, %45, %46, %47, %48, %49, %50, %51, %52, %53, %54, %55, %56, %57, %58, %59, %60, %61, %62, %63, %64, %65, %66, %67, %68, %69, %70, %71, %72, %73, %74, %75, %76, %77, %78, %79, %80, %81, %82, %83, %84, %85, %86, %87, %88, %89, %90, %91, %92, %93, %94, %95}, {%96, %97, %98, %99}, %100, p, 1, 1, 1;\n}"
    : "+f"(d[0]), "+f"(d[1]), "+f"(d[2]), "+f"(d[3]), "+f"(d[4]), "+f"(d[5]), "+f"(d[6]), "+f"(d[7]), "+f"(d[8]), "+f"(d[9]), "+f"(d[10]), "+f"(d[11]), "+f"(d[12]), "+f"(d[13]), "+f"(d[14]), "+f"(d[15]), "+f"(d[16]), "+f"(d[17]), "+f"(d[18]), "+f"(d[19]), "+f"(d[20]), "+f"(d[21]), "+f"(d[22]), "+f"(d[23]), "+f"(d[24]), "+f"(d[25]), "+f"(d[26]), "+f"(d[27]), "+f"(d[28]), "+f"(d[29]), "+f"(d[30]), "+f"(d[31]), "+f"(d[32]), "+f"(d[33]), "+f"(d[34]), "+f"(d[35]), "+f"(d[36]), "+f"(d[37]), "+f"(d[38]), "+f"(d[39]), "+f"(d[40]), "+f"(d[41]), "+f"(d[42]), "+f"(d[43]), "+f"(d[44]), "+f"(d[45]), "+f"(d[46]), "+f"(d[47]), "+f"(d[48]), "+f"(d[49]), "+f"(d[50]), "+f"(d[51]), "+f"(d[52]), "+f"(d[53]), "+f"(d[54]), "+f"(d[55]), "+f"(d[56]), "+f"(d[57]), "+f"(d[58]), "+f"(d[59]), "+f"(d[60]), "+f"(d[61]), "+f"(d[62]), "+f"(d[63]), "+f"(d[64]), "+f"(d[65]), "+f"(d[66]), "+f"(d[67]), "+f"(d[68]), "+f"(d[69]), "+f"(d[70]), "+f"(d[71]), "+f"(d[72]), "+f"(d[73]), "+f"(d[74]), "+f"(d[75]), "+f"(d[76]), "+f"(d[77]), "+f"(d[78]), "+f"(d[79]), "+f"(d[80]), "+f"(d[81]), "+f"(d[82]), "+f"(d[83]), "+f"(d[84]), "+f"(d[85]), "+f"(d[86]), "+f"(d[87]), "+f"(d[88]), "+f"(d[89]), "+f"(d[90]), "+f"(d[91]), "+f"(d[92]), "+f"(d[93]), "+f"(d[94]), "+f"(d[95])
    : "r"(a0), "r"(a1), "r"(a2), "r"(a3), "l"(db), "r"(scale_d));
}

__device__ __forceinline__ void wgmma_rs_n48_t1(float (&d)[24], uint32_t a0, uint32_t a1, uint32_t a2, uint32_t a3, uint64_t db, int scale_d) {
  asm volatile("{\n.reg .pred p;\nsetp.ne.b32 p, %29, 0;\nwgmma.mma_async.sync.aligned.m64n48k16.f32.bf16.bf16 {%0, %1, %2, %3, %4, %5, %6, %7, %8, %9, %10, %11, %12, %13, %14, %15, %16, %17, %18, %19, %20, %21, %22, %23}, {%24, %25, %26, %27}, %28, p, 1, 1, 1;\n}"
    : "+f"(d[0]), "+f"(d[1]), "+f"(d[2]), "+f"(d[3]), "+f"(d[4]), "+f"(d[5]), "+f"(d[6]), "+f"(d[7]), "+f"(d[8]), "+f"(d[9]), "+f"(d[10]), "+f"(d[11]), "+f"(d[12]), "+f"(d[13]), "+f"(d[14]), "+f"(d[15]), "+f"(d[16]), "+f"(d[17]), "+f"(d[18]), "+f"(d[19]), "+f"(d[20]), "+f"(d[21]), "+f"(d[22]), "+f"(d[23])
    : "r"(a0), "r"(a1), "r"(a2), "r"(a3), "l"(db), "r"(scale_d));
}

__device__ __forceinline__ void wgmma_rs_n128_t0(float (&d)[64], uint32_t a0, uint32_t a1, uint32_t a2, uint32_t a3, uint64_t db, int scale_d) {
  asm volatile("{\n.reg .pred p;\nsetp.ne.b32 p, %69, 0;\nwgmma.mma_async.sync.aligned.m64n128k16.f32.bf16.bf16 {%0, %1, %2, %3, %4, %5, %6, %7, %8, %9, %10, %11, %12, %13, %14, %15, %16, %17, %18, %19, %20, %21, %22, %23, %24, %25, %26, %27, %28, %29, %30, %31, %32, %33, %34, %35, %36, %37, %38, %39, %40, %41, %42, %43, %44, %45, %46, %47, %48, %49, %50, %51, %52, %53, %54, %55, %56, %57, %58, %59, %60, %61, %62, %63}, {%64, %65, %66, %67}, %68, p, 1, 1, 0;\n}"
    : "+f"(d[0]), "+f"(d[1]), "+f"(d[2]), "+f"(d[3]), "+f"(d[4]), "+f"(d[5]), "+f"(d[6]), "+f"(d[7]), "+f"(d[8]), "+f"(d[9]), "+f"(d[10]), "+f"(d[11]), "+f"(d[12]), "+f"(d[13]), "+f"(d[14]), "+f"(d[15]), "+f"(d[16]), "+f"(d[17]), "+f"(d[18]), "+f"(d[19]), "+f"(d[20]), "+f"(d[21]), "+f"(d[22]), "+f"(d[23]), "+f"(d[24]), "+f"(d[25]), "+f"(d[26]), "+f"(d[27]), "+f"(d[28]), "+f"(d[29]), "+f"(d[30]), "+f"(d[31]), "+f"(d[32]), "+f"(d[33]), "+f"(d[34]), "+f"(d[35]), "+f"(d[36]), "+f"(d[37]), "+f"(d[38]), "+f"(d[39]), "+f"(d[40]), "+f"(d[41]), "+f"(d[42]), "+f"(d[43]), "+f"(d[44]), "+f"(d[45]), "+f"(d[46]), "+f"(d[47]), "+f"(d[48]), "+f"(d[49]), "+f"(d[50]), "+f"(d[51]), "+f"(d[52]), "+f"(d[53]), "+f"(d[54]), "+f"(d[55]), "+f"(d[56]), "+f"(d[57]), "+f"(d[58]), "+f"(d[59]), "+f"(d[60]), "+f"(d[61]), "+f"(d[62]), "+f"(d[63])
    : "r"(a0), "r"(a1), "r"(a2), "r"(a3), "l"(db), "r"(scale_d));
}

__device__ __forceinline__ void wgmma_rs_n24_t1(float (&d)[12], uint32_t a0, uint32_t a1, uint32_t a2, uint32_t a3, uint64_t db, int scale_d) {
  asm volatile("{\n.reg .pred p;\nsetp.ne.b32 p, %17, 0;\nwgmma.mma_async.sync.aligned.m64n24k16.f32.bf16.bf16 {%0, %1, %2, %3, %4, %5, %6, %7, %8, %9, %10, %11}, {%12, %13, %14, %15}, %16, p, 1, 1, 1;\n}"
    : "+f"(d[0]), "+f"(d[1]), "+f"(d[2]), "+f"(d[3]), "+f"(d[4]), "+f"(d[5]), "+f"(d[6]), "+f"(d[7]), "+f"(d[8]), "+f"(d[9]), "+f"(d[10]), "+f"(d[11])
    : "r"(a0), "r"(a1), "r"(a2), "r"(a3), "l"(db), "r"(scale_d));
}

__device__ __forceinline__ void wgmma_ss_n80_t1(float (&d)[40], uint64_t da, uint64_t db, int scale_d) {
  asm volatile("{\n.reg .pred p;\nsetp.ne.b32 p, %42, 0;\nwgmma.mma_async.sync.aligned.m64n80k16.f32.bf16.bf16 {%0, %1, %2, %3, %4, %5, %6, %7, %8, %9, %10, %11, %12, %13, %14, %15, %16, %17, %18, %19, %20, %21, %22, %23, %24, %25, %26, %27, %28, %29, %30, %31, %32, %33, %34, %35, %36, %37, %38, %39}, %40, %41, p, 1, 1, 0, 1;\n}"
    : "+f"(d[0]), "+f"(d[1]), "+f"(d[2]), "+f"(d[3]), "+f"(d[4]), "+f"(d[5]), "+f"(d[6]), "+f"(d[7]), "+f"(d[8]), "+f"(d[9]), "+f"(d[10]), "+f"(d[11]), "+f"(d[12]), "+f"(d[13]), "+f"(d[14]), "+f"(d[15]), "+f"(d[16]), "+f"(d[17]), "+f"(d[18]), "+f"(d[19]), "+f"(d[20]), "+f"(d[21]), "+f"(d[22]), "+f"(d[23]), "+f"(d[24]), "+f"(d[25]), "+f"(d[26]), "+f"(d[27]), "+f"(d[28]), "+f"(d[29]), "+f"(d[30]), "+f"(d[31]), "+f"(d[32]), "+f"(d[33]), "+f"(d[34]), "+f"(d[35]), "+f"(d[36]), "+f"(d[37]), "+f"(d[38]), "+f"(d[39])
    : "l"(da), "l"(db), "r"(scale_d));
}

__device__ __forceinline__ void wgmma_ss_n192_t1(float (&d)[96], uint64_t da, uint64_t db, int scale_d) {
  asm volatile("{\n.reg .pred p;\nsetp.ne.b32 p, %98, 0;\nwgmma.mma_async.sync.aligned.m64n192k16.f32.bf16.bf16 {%0, %1, %2, %3, %4, %5, %6, %7, %8, %9, %10, %11, %12, %13, %14, %15, %16, %17, %18, %19, %20, %21, %22, %23, %24, %25, %26, %27, %28, %29, %30, %31, %32, %33, %34, %35, %36, %37, %38, %39, %40, %41, %42, %43, %44, %45, %46, %47, %48, %49, %50, %51, %52, %53, %54, %55, %56, %57, %58, %59, %60, %61, %62, %63, %64, %65, %66, %67, %68, %69, %70, %71, %72, %73, %74, %75, %76, %77, %78, %79, %80, %81, %82, %83, %84, %85, %86, %87, %88, %89, %90, %91, %92, %93, %94, %95}, %96, %97, p, 1, 1, 0, 1;\n}"
    : "+f"(d[0]), "+f"(d[1]), "+f"(d[2]), "+f"(d[3]), "+f"(d[4]), "+f"(d[5]), "+f"(d[6]), "+f"(d[7]), "+f"(d[8]), "+f"(d[9]), "+f"(d[10]), "+f"(d[11]), "+f"(d[12]), "+f"(d[13]), "+f"(d[14]), "+f"(d[15]), "+f"(d[16]), "+f"(d[17]), "+f"(d[18]), "+f"(d[19]), "+f"(d[20]), "+f"(d[21]), "+f"(d[22]), "+f"(d[23]), "+f"(d[24]), "+f"(d[25]), "+f"(d[26]), "+f"(d[27]), "+f"(d[28]), "+f"(d[29]), "+f"(d[30]), "+f"(d[31]), "+f"(d[32]), "+f"(d[33]), "+f"(d[34]), "+f"(d[35]), "+f"(d[36]), "+f"(d[37]), "+f"(d[38]), "+f"(d[39]), "+f"(d[40]), "+f"(d[41]), "+f"(d[42]), "+f"(d[43]), "+f"(d[44]), "+f"(d[45]), "+f"(d[46]), "+f"(d[47]), "+f"(d[48]), "+f"(d[49]), "+f"(d[50]), "+f"(d[51]), "+f"(d[52]), "+f"(d[53]), "+f"(d[54]), "+f"(d[55]), "+f"(d[56]), "+f"(d[57]), "+f"(d[58]), "+f"(d[59]), "+f"(d[60]), "+f"(d[61]), "+f"(d[62]), "+f"(d[63]), "+f"(d[64]), "+f"(d[65]), "+f"(d[66]), "+f"(d[67]), "+f"(d[68]), "+f"(d[69]), "+f"(d[70]), "+f"(d[71]), "+f"(d[72]), "+f"(d[73]), "+f"(d[74]), "+f"(d[75]), "+f"(d[76]), "+f"(d[77]), "+f"(d[78]), "+f"(d[79]), "+f"(d[80]), "+f"(d[81]), "+f"(d[82]), "+f"(d[83]), "+f"(d[84]), "+f"(d[85]), "+f"(d[86]), "+f"(d[87]), "+f"(d[88]), "+f"(d[89]), "+f"(d[90]), "+f"(d[91]), "+f"(d[92]), "+f"(d[93]), "+f"(d[94]), "+f"(d[95])
    : "l"(da), "l"(db), "r"(scale_d));
}

__device__ __forceinline__ void wgmma_ss_n64_t1(float (&d)[32], uint64_t da, uint64_t db, int scale_d) {
  asm volatile("{\n.reg .pred p;\nsetp.ne.b32 p, %34, 0;\nwgmma.mma_async.sync.aligned.m64n64k16.f32.bf16.bf16 {%0, %1, %2, %3, %4, %5, %6, %7, %8, %9, %10, %11, %12, %13, %14, %15, %16, %17, %18, %19, %20, %21, %22, %23, %24, %25, %26, %27, %28, %29, %30, %31}, %32, %33, p, 1, 1, 0, 1;\n}"
    : "+f"(d[0]), "+f"(d[1]), "+f"(d[2]), "+f"(d[3]), "+f"(d[4]), "+f"(d[5]), "+f"(d[6]), "+f"(d[7]), "+f"(d[8]), "+f"(d[9]), "+f"(d[10]), "+f"(d[11]), "+f"(d[12]), "+f"(d[13]), "+f"(d[14]), "+f"(d[15]), "+f"(d[16]), "+f"(d[17]), "+f"(d[18]), "+f"(d[19]), "+f"(d[20]), "+f"(d[21]), "+f"(d[22]), "+f"(d[23]), "+f"(d[24]), "+f"(d[25]), "+f"(d[26]), "+f"(d[27]), "+f"(d[28]), "+f"(d[29]), "+f"(d[30]), "+f"(d[31])
    : "l"(da), "l"(db), "r"(scale_d));
}

struct Params {
  const __nv_bfloat16* x; const __nv_bfloat16* wqkv; const __nv_bfloat16* wo; const __nv_bfloat16* w1;
  const __nv_bfloat16* b1; const __nv_bfloat16* w2; const __nv_bfloat16* b2; __nv_bfloat16* out;
};
constexpr float SM_SCALE = 0.22360679774997896f * 1.4426950408889634f;

__global__ void __launch_bounds__(384, 1)
fused_block_kernel(const __grid_constant__ CUtensorMap mX, const __grid_constant__ CUtensorMap mWq, const __grid_constant__ CUtensorMap mWr,
                   const __grid_constant__ CUtensorMap mWo, const __grid_constant__ CUtensorMap mW1, const __grid_constant__ CUtensorMap mW2,
                   const __grid_constant__ CUtensorMap mW2r, const Params p) {
  extern __shared__ __align__(1024) uint8_t smem_raw[];
  const uint32_t sb = smem_u32(smem_raw);
  const int tid = threadIdx.x, warp = tid >> 5, lane = tid & 31;
  const int cta = blockIdx.x, rank = cta & 1, pair = cta >> 1;
  const int hq = pair & 7, rbA = (pair >> 3) * 2 + rank;
  const int rbC = pair >> 2, jj = pair & 3, j = jj * 2 + rank;
  auto bar = [&](int i) { return sb + BARS + i * 8; };

  if (warp == 0) {
    if (lane == 0) PROF_T(0);
    #pragma unroll
    for (int u = 0; u < 2; u++) {
      const int i = lane + 32 * u;
      const unsigned long long pk = u ? ((lane & 16) ? BAR_PK3 : BAR_PK2) : ((lane & 16) ? BAR_PK1 : BAR_PK0);
      if (i < B_COUNT) mbar_init(bar(i), (uint32_t)(pk >> ((lane & 15) * 4)) & 15u);
    }
    asm volatile("fence.mbarrier_init.release.cluster;" ::: "memory");
  } else if (warp == 8 && lane == 0) {
    prefetch_map(&mWq); prefetch_map(&mWr); prefetch_map(&mX);
  }
  __syncthreads();
  cluster_arrive();

  if (warp >= 8) {
    asm volatile("setmaxnreg.dec.sync.aligned.u32 56;");
    if (warp == 8) {
      cluster_wait();
      if (lane == 0) {
        #pragma unroll 1
        for (int it = 0; it < 10; it++) {
          const int s = it & 3;
          if (it >= 4) mbar_wait(bar(B_AEMPTY + s), ((it >> 2) - 1) & 1);
          const uint32_t full = bar(B_AFULL + s), dst = sb + s * A_STAGE + 16384 + rank * 15360;
          mbar_expect_tx(full, 30720);
          tma_3d_mc(dst, &mWq, 80 * hq, it * 64 + 32 * rank, 0, full);
          tma_3d_mc(dst + 12288, &mWr, 80 * hq + 64, it * 64 + 32 * rank, 0, full);
        }
        prefetch_map(&mWo); prefetch_map(&mW1); prefetch_map(&mW2); prefetch_map(&mW2r);
        mbar_wait(bar(B_AEMPTY + 2), 1); mbar_wait(bar(B_AEMPTY + 3), 1); mbar_wait(bar(B_AEMPTY + 0), 0); mbar_wait(bar(B_AEMPTY + 1), 0);
        mbar_wait(bar(B_AUXDONE), 0);
        if (rbA > 0) mbar_wait(bar(B_KVFULL), 0);
        mbar_expect_tx(bar(B_WOFULL), 81920);
        #pragma unroll 1
        for (int kb = 0; kb < 4; kb++) tma_3d(sb + WO_OFF + kb * 20480, &mWo, 0, kb * 128, 5 * j, bar(B_WOFULL));
        mbar_wait(bar(B_ATTDONE), 0); mbar_wait(bar(B_KVST), 0);
        mbar_expect_tx(bar(B_WO4), 20480);
        tma_3d(sb + WO4_OFF, &mWo, 0, 512, 5 * j, bar(B_WO4));
        mbar_wait(bar(B_AUX2), 0);
        mbar_wait(bar(B_CDONE), 0);
        #pragma unroll 1
        for (int t = 0; t < 8; t++) {
          const int s = t & 3;
          if (t >= 4) mbar_wait(bar(B_DBEMPTY + s), 0);
          const int kt = t < 2 ? (j ^ t) : (((jj + (t >> 1)) & 3) * 2 + (t & 1));
          const uint32_t full = bar(B_DBFULL + s), dst = sb + DB_OFF + s * DB_SLOT;
          mbar_expect_tx(full, 30720);
          #pragma unroll 1
          for (int c = 0; c < 3; c++) tma_2d(dst + c * 10240, &mW1, 192 * j + 64 * c, 80 * kt, full);
        }
        #pragma unroll 1
        for (int i = 0; i < 12; i++) {
          const int s = i % 5;
          if (i < 4) mbar_wait(bar(B_DBEMPTY + i), 1);
          else if (i >= 5) mbar_wait(bar(B_EBEMPTY + s), (i / 5 - 1) & 1);
          const int ks = i % 6;
          const int krow = 384 * jj + (ks < 3 ? 192 * rank + 64 * ks : 192 * (rank ^ 1) + 64 * (ks - 3));
          const uint32_t full = bar(B_EBFULL + s), dst = sb + EB_OFF + s * EB_SLOT;
          if (i < 6) {
            mbar_expect_tx(full, 24576);
            #pragma unroll 1
            for (int c = 0; c < 3; c++) tma_2d(dst + c * 8192, &mW2, 160 * ((jj + 1 + c) & 3) + 80 * rank, krow, full);
          } else {
            mbar_expect_tx(full, 16384);
            tma_2d(dst, &mW2, 160 * jj + 80 * rank, krow, full);
            #pragma unroll 1
            for (int c = 0; c < 4; c++) tma_2d(dst + 8192 + c * 2048, &mW2r, 160 * ((jj + 1 + c) & 3) + 80 * rank + 64, krow, full);
          }
        }
      }
    } else if (warp == 9) {
      if (lane == 0) {
        #pragma unroll 1
        for (int it = 0; it < 4; it++) { mbar_expect_tx(bar(B_AFULL + it), 16384); tma_2d(sb + it * A_STAGE, &mX, it * 64, rbA * 128, bar(B_AFULL + it)); }
      }
      __syncwarp();
      cluster_wait();
      if (lane == 0) {
        #pragma unroll 1
        for (int it = 4; it < 10; it++) {
          const int s = it & 3;
          mbar_wait(bar(B_AEMPTY + s), ((it >> 2) - 1) & 1);
          mbar_expect_tx(bar(B_AFULL + s), 16384);
          tma_2d(sb + s * A_STAGE, &mX, it * 64, rbA * 128, bar(B_AFULL + s));
        }
        mbar_wait(bar(B_AEMPTY + 2), 1); mbar_wait(bar(B_AEMPTY + 3), 1); mbar_wait(bar(B_AEMPTY + 0), 0); mbar_wait(bar(B_AEMPTY + 1), 0);
      }
      __syncwarp();
      mbar_wait(bar(B_EPOCH), 0);
      const unsigned tag = lds_u32(sb + S_EPOCH);
      if (lane == 0) {
        #pragma unroll 1
        for (int d = 1; d <= 2; d++) {
          if (rbA >= d) {
            wait_flag(&g_flags[FL_KV + (rbA - d) * 8 + hq], tag);
            fence_async_all();
            mbar_expect_tx(bar(B_KVFULL + d - 1), KV_BLK);
            bulk_ld(sb + (d == 1 ? KV_PREV : KV_FAR), &g_kv[((rbA - d) * 8 + hq) * (KV_BLK / 16)], KV_BLK, bar(B_KVFULL + d - 1));
          }
        }
        PROF_T(20);
        mbar_wait(bar(B_ATTDONE), 0); mbar_wait(bar(B_KVST), 0);
      }
      __syncwarp();
      {
        int next = 0; unsigned n = 0;
        while (next < 8) {
          const unsigned v = ld_relaxed(&g_flags[FL_O + rbC * 8 + (lane & 7)]);
          const unsigned ready = __ballot_sync(~0u, (int)(v - tag * 8u) >= 0);
          while (next < 8 && ((ready >> next) & 1)) {
            if (lane == 0) {
              const int s = next < 5 ? next : next - 5;
              if (next >= 5) mbar_wait(bar(B_CEMPTY + s), 0);
              fence_async_all();
              mbar_expect_tx(bar(B_CFULL + s), OT_BYTES);
              bulk_ld_mc(sb + s * OT_BYTES + rank * 10240, reinterpret_cast<const uint8_t*>(&g_o[(rbC * 8 + next) * (OT_BYTES / 16)]) + rank * 10240, 10240, bar(B_CFULL + s));
            }
            next++;
          }
          spin_guard(n);
        }
      }
      if (lane == 0) {
        PROF_T(21);
        mbar_expect_tx(bar(B_DAFULL + 1), HT_BYTES);
        for (int i = 0; i < 3; i++) mbar_expect_tx(bar(B_FFULL + i), 16384);
        mbar_wait(bar(B_CDONE), 0);
      }
      __syncwarp();
      {
        int next = 2; unsigned n = 0;
        while (next < 8) {
          const unsigned v = ld_relaxed(&g_flags[FL_H + rbC * 8 + (lane & 7)]);
          const unsigned ready = __ballot_sync(~0u, (int)(v - tag) >= 0);
          while (next < 8) {
            const int kt = ((jj + (next >> 1)) & 3) * 2 + (next & 1);
            if (!((ready >> kt) & 1)) break;
            if (lane == 0) {
              const int s = next & 3;
              if (next >= 4) mbar_wait(bar(B_DAEMPTY + s), 0);
              if (next == 4) mbar_wait(bar(B_DAEMPTY + 1), 0);
              fence_async_all();
              mbar_expect_tx(bar(B_DAFULL + s), HT_BYTES);
              bulk_ld_mc(sb + s * HT_BYTES + rank * 10752, reinterpret_cast<const uint8_t*>(&g_h[(rbC * 8 + kt) * (HT_BYTES / 16)]) + rank * 10752, 10752, bar(B_DAFULL + s));
            }
            next++;
          }
          spin_guard(n);
        }
        if (lane == 0) PROF_T(22);
      }
    } else if (warp == 10) {
      cluster_wait();
      unsigned tag = 0;
      if (lane == 0) {
        tag = ld_relaxed(&g_flags[FL_EPOCH + cta]) + 1u;
        st_relaxed(&g_flags[FL_EPOCH + cta], tag);
        sts_u32(sb + S_EPOCH, tag);
        mbar_arrive(bar(B_EPOCH));
      }
      tag = __shfl_sync(~0u, tag, 0);
      #pragma unroll 1
      for (int job = 0; job < 2; job++) {
        const int n = job ? 192 : 240;
        const unsigned long long* src = job ? &g_cs[3 * DM + 192 * j] : &g_cs[80 * hq];
        unsigned long long v[8]; unsigned spins = 0;
        while (true) {
          bool ok = true;
          #pragma unroll
          for (int i = 0; i < 8; i++) {
            const int c = lane + 32 * i;
            if (c < n) v[i] = ld_relaxed64(src + c + (job ? 0 : (c >= 80 ? 560 : 0) + (c >= 160 ? 560 : 0)));
          }
          #pragma unroll
          for (int i = 0; i < 8; i++) if (lane + 32 * i < n) ok = ok && (unsigned)(v[i] >> 32) == tag;
          if (__all_sync(~0u, ok)) break;
          spin_guard(spins);
        }
        #pragma unroll
        for (int i = 0; i < 8; i++) {
          const int c = lane + 32 * i;
          if (c < n) {
            sts_u32(sb + (job ? S_CS2 + c * 8 : S_CS1 + c * 4), (unsigned)v[i]);
            if (job) sts_u32(sb + S_CS2 + c * 8 + 4, (uint32_t)__bfloat16_as_ushort(p.b1[192 * j + c]) << 16);
          }
        }
        __syncwarp();
        if (lane == 0) {
          mbar_arrive(bar(job ? B_CS2 : B_STAT));
          if (job == 0) {
            PROF_T(23);
            mbar_wait(bar(B_KVW), 0);
            bulk_st(&g_kv[(rbA * 8 + hq) * (KV_BLK / 16)], sb + KV_OWN, KV_BLK);
            bulk_commit(); bulk_wait0();
            fence_async_all();
            st_release(&g_flags[FL_KV + rbA * 8 + hq], tag);
            mbar_arrive(bar(B_KVST));
            PROF_T(24);
          }
        }
        __syncwarp();
      }
      if (lane == 0) {
        mbar_wait(bar(B_HW), 0);
        mbar_arrive(bar(B_DAFULL + 0));
        bulk_st(&g_h[(rbC * 8 + j) * (HT_BYTES / 16)], sb, HT_BYTES);
        bulk_commit();
        mbar_wait(bar(B_CDONE), 0);
        bulk_dsmem(mapa(sb + HT_BYTES, rank ^ 1), sb, HT_BYTES, mapa(bar(B_DAFULL + 1), rank ^ 1));
        bulk_wait0();
        fence_async_all();
        st_release(&g_flags[FL_H + rbC * 8 + j], tag);
        mbar_arrive_cluster(bar(B_DAEMPTY + 0), 0); mbar_arrive_cluster(bar(B_DAEMPTY + 0), 1);
        PROF_T(25);
        mbar_wait(bar(B_FW), 0); mbar_wait(bar(B_DDONE), 0);
        #pragma unroll 1
        for (int i = 0; i < 3; i++) {
          const uint32_t off = rank * 49152 + i * 16384;
          bulk_dsmem(mapa(sb + off, rank ^ 1), sb + off, 16384, mapa(bar(B_FFULL + i), rank ^ 1));
        }
      }
    } else {
      cluster_wait();
      #pragma unroll 1
      for (int job = 0; job < 2; job++) {
        if (job) mbar_wait(bar(B_KVW), 0);
        if (cta < (job ? 96 : 120)) {
          const int ld = job ? FF : 3 * DM, batch = job ? 256 : 640;
          const __nv_bfloat16* src = (job ? p.w1 : p.wqkv) + (size_t)(lane >> 1) * ld + cta * 16 + (lane & 1) * 8;
          const uint32_t sl = sb + (job ? CS_STG1 : CS_STG0) + lane * 16;
          float acc[8];
          #pragma unroll
          for (int i = 0; i < 8; i++) acc[i] = 0.f;
          #pragma unroll 1
          for (int r0 = 0; r0 < DM; r0 += batch) {
            const int n = (DM - r0 < batch ? DM - r0 : batch) >> 4;
            #pragma unroll 1
            for (int i = 0; i < n; i++) cp_async16(sl + i * 512, src + (size_t)(r0 + i * 16) * ld);
            cp_async_wait_all();
            #pragma unroll 2
            for (int i = 0; i < n; i++) {
              const uint4 v = lds_u4(sl + i * 512);
              acc[0] += bf_lo(v.x); acc[1] += bf_hi(v.x); acc[2] += bf_lo(v.y); acc[3] += bf_hi(v.y);
              acc[4] += bf_lo(v.z); acc[5] += bf_hi(v.z); acc[6] += bf_lo(v.w); acc[7] += bf_hi(v.w);
            }
          }
          #pragma unroll 1
          for (int o = 2; o < 32; o <<= 1) {
            #pragma unroll
            for (int i = 0; i < 8; i++) acc[i] += __shfl_xor_sync(~0u, acc[i], o);
          }
          float v = acc[0];
          #pragma unroll
          for (int i = 1; i < 8; i++) v = (lane >> 1) == i ? acc[i] : v;
          mbar_wait(bar(B_EPOCH), 0);
          const unsigned tag = lds_u32(sb + S_EPOCH);
          if (lane < 16) st_relaxed64(&g_cs[(job ? 3 * DM : 0) + cta * 16 + (lane & 1) * 8 + (lane >> 1)], __float_as_uint(v), tag);
        }
        __syncwarp();
        if (lane == 0) {
          mbar_arrive(bar(job ? B_AUX2 : B_AUXDONE));
          if (job == 0) {
            PROF_T(26);
            prefetch_l2(reinterpret_cast<const uint8_t*>(p.wo) + cta * 6400, 6400);
            prefetch_l2(reinterpret_cast<const uint8_t*>(p.w1) + cta * 15360, 15360);
            prefetch_l2(reinterpret_cast<const uint8_t*>(p.w2) + cta * 15360, 15360);
          }
        }
      }
    }
  } else {
    cluster_wait();
    asm volatile("setmaxnreg.inc.sync.aligned.u32 224;");
    const int wg = warp >> 2, g = lane >> 2, c4 = lane & 3;
    auto release_pair = [&](int b) { if ((tid & 127) < 2) mbar_arrive_cluster(bar(b), tid & 1); };
    const int rbw = warp < 4 ? warp : 11 - warp;
    uint32_t qf[10][2];
    {
      float acc[96], acr[24];
      float sx0 = 0.f, sq0 = 0.f, sx1 = 0.f, sq1 = 0.f;
      const uint32_t arow = rbw * 16 + (lane & 7) + ((lane >> 3) & 1) * 8;
      const uint32_t aoff = arow * 128 + (((lane >> 4) ^ (arow & 7)) << 4);
      #pragma unroll 1
      for (int it = 0; it < 10; it++) {
        const int s = it & 3;
        mbar_wait(bar(B_AFULL + s), (it >> 2) & 1);
        if (it == 0 && tid == 0) PROF_T(1);
        const uint32_t a = sb + s * A_STAGE, b = a + 16384;
        uint32_t af[4][4];
        #pragma unroll
        for (int kk = 0; kk < 4; kk++) ldsm4(a + (aoff ^ (kk * 32)), af[kk]);
        wg_fence();
        #pragma unroll
        for (int kk = 0; kk < 4; kk++) {
          const uint32_t bb = b + (kk >> 1) * 15360;
          const int sc = (it > 0 || kk > 0) ? 1 : 0;
          wgmma_rs_n192_t1(acc, af[kk][0], af[kk][1], af[kk][2], af[kk][3], make_desc(bb + (kk & 1) * 2048, 4096, 1024, 1), sc);
          wgmma_rs_n48_t1(acr, af[kk][0], af[kk][1], af[kk][2], af[kk][3], make_desc(bb + 12288 + (kk & 1) * 512, 1024, 256, 3), sc);
        }
        wg_commit();
        #pragma unroll
        for (int kk = 0; kk < 4; kk++) {
          #pragma unroll
          for (int u = 0; u < 4; u++) {
            const float lo = bf_lo(af[kk][u]), hi = bf_hi(af[kk][u]);
            if (u & 1) { sx1 += lo + hi; sq1 = fmaf(lo, lo, fmaf(hi, hi, sq1)); }
            else { sx0 += lo + hi; sq0 = fmaf(lo, lo, fmaf(hi, hi, sq0)); }
          }
        }
        wg_wait<0>();
        #pragma unroll
        for (int kk = 0; kk < 4; kk++) asm volatile("" :: "r"(af[kk][0]), "r"(af[kk][1]), "r"(af[kk][2]), "r"(af[kk][3]));
        release_pair(B_AEMPTY + s);
      }
      reg_fence(acc); reg_fence(acr);
      if (tid == 0) PROF_T(2);
      const float mu0 = quad_sum(sx0) * (1.f / DM), mu1 = quad_sum(sx1) * (1.f / DM);
      const float rs0 = rsq(fmaxf(quad_sum(sq0) * (1.f / DM) - mu0 * mu0, 0.f) + 1e-5f), rs1 = rsq(fmaxf(quad_sum(sq1) * (1.f / DM) - mu1 * mu1, 0.f) + 1e-5f);
      const float mr0 = -mu0 * rs0, mr1 = -mu1 * rs1;
      mbar_wait(bar(B_STAT), 0);
      named_sync(1, 256);
      auto norm2 = [&](int sec, int t, uint32_t& lo, uint32_t& hi) {
        const float2 cs = lds_f2(sb + S_CS1 + (80 * sec + 8 * t + 2 * c4) * 4);
        const float* a = t < 8 ? &acc[4 * (8 * sec + t)] : &acr[4 * (2 * sec + t - 8)];
        lo = pack2(fmaf(a[0], rs0, cs.x * mr0), fmaf(a[1], rs0, cs.y * mr0));
        hi = pack2(fmaf(a[2], rs1, cs.x * mr1), fmaf(a[3], rs1, cs.y * mr1));
      };
      const uint32_t stA = sb + KV_OWN + (uint32_t)(rbw * 16 + ((lane >> 3) & 1) * 8 + (lane & 7)) * 16 + (uint32_t)(lane >> 4) * 2048;
      #pragma unroll
      for (int i = 0; i < 5; i++) {
        uint32_t a0, a1, a2, a3;
        norm2(1, 2 * i, a0, a1); norm2(1, 2 * i + 1, a2, a3);
        stsm4(stA + i * 4096, a0, a1, a2, a3);
      }
      #pragma unroll
      for (int P = 0; P < 2; P++) {
        uint32_t a0, a1, a2, a3;
        norm2(2, 5 * P, a0, a1); norm2(2, 5 * P + 1, a2, a3);
        stsm4(stA + 20480 + P * 12288, a0, a1, a2, a3);
        norm2(2, 5 * P + 2, a0, a1);
        const uint32_t one_e = c4 == 2 ? 0x3F80u : 0u, one_o = c4 == 0 ? 0x3F80u : 0u;
        stsm4(stA + 20480 + P * 12288 + 4096, c4 < 2 ? a0 : one_e, c4 < 2 ? a1 : one_e, c4 < 2 ? one_o : a0, c4 < 2 ? one_o : a1);
        norm2(2, 5 * P + 3, a0, a1); norm2(2, 5 * P + 4, a2, a3);
        stsm4(stA + 20480 + P * 12288 + 8192, a0, a1, a2, a3);
      }
      fence_async();
      __syncwarp();
      if (lane == 0) mbar_arrive(bar(B_KVW));
      #pragma unroll
      for (int i = 0; i < 10; i++) norm2(0, i, qf[i][0], qf[i][1]);
      named_sync(1, 256);
      if (tid == 0) PROF_T(3);
    }
    {
      float O[12], m0 = 0.f, m1 = 0.f, sv[3][14];
      uint32_t qa[8];
      const bool lowq = c4 < 2, k0 = 2 * c4 <= g, k1 = 2 * c4 + 1 <= g;
      uint8_t* og = reinterpret_cast<uint8_t*>(&g_o[(rbA * 8 + hq) * (OT_BYTES / 16)]) + (rbw * 16 + g) * 16 + c4 * 4;
      #pragma unroll 1
      for (int step = 0; step < 12; step++) {
        const int h = step < 4 ? step : 3 - ((step - 4) >> 1), st = step < 4 ? 0 : 1 + (step & 1), odd = h & 1;
        if (step < 4 || (st == 1 && h < 3)) {
          wg_wait<0>();
          reg_fence(O);
          const uint32_t ml = lowq ? ~0u : 0u;
          if (h == 0)      { qa[0] = qf[0][0]; qa[1] = qf[0][1]; qa[2] = qf[1][0]; qa[3] = qf[1][1]; qa[4] = qf[2][0] & ml; qa[5] = qf[2][1] & ml; qa[6] = 0u; qa[7] = 0u; }
          else if (h == 1) { qa[0] = 0u; qa[1] = 0u; qa[2] = qf[2][0] & ~ml; qa[3] = qf[2][1] & ~ml; qa[4] = qf[3][0]; qa[5] = qf[3][1]; qa[6] = qf[4][0]; qa[7] = qf[4][1]; }
          else if (h == 2) { qa[0] = qf[5][0]; qa[1] = qf[5][1]; qa[2] = qf[6][0]; qa[3] = qf[6][1]; qa[4] = qf[7][0] & ml; qa[5] = qf[7][1] & ml; qa[6] = 0u; qa[7] = 0u; }
          else             { qa[0] = 0u; qa[1] = 0u; qa[2] = qf[7][0] & ~ml; qa[3] = qf[7][1] & ~ml; qa[4] = qf[8][0]; qa[5] = qf[8][1]; qa[6] = qf[9][0]; qa[7] = qf[9][1]; }
          if (step < 4) {
            m0 = m1 = -INFINITY;
            #pragma unroll
            for (int i = 0; i < 12; i++) O[i] = 0.f;
          } else {
            #pragma unroll
            for (int q = 0; q < 3; q++) if (h == q) {
              #pragma unroll
              for (int i = 0; i < 12; i++) O[i] = sv[q][i];
              m0 = sv[q][12]; m1 = sv[q][13];
            }
          }
        }
        if (st <= rbA) {
          if (st > 0) mbar_wait(bar(B_KVFULL + st - 1), 0);
          if (step == 4 && tid == 0) PROF_T(5);
          const uint32_t kv = sb + (st == 0 ? KV_OWN : st == 1 ? KV_PREV : KV_FAR);
          const uint32_t kb = kv + (5 * (h >> 1) + odd) * 2048, vb = kv + 20480 + h * 6144;
          const int lo = st == 2 ? rbw : 0, hi = st == 0 ? rbw : 7, mblk = st == 1 ? -1 : rbw;
          const bool far = st == 2, pa = k0 != far, pb = k1 != far;
          float s[64];
          if (tid == 0 && (step == 6 || step == 7)) PROF_T(27 + (step - 6) * 5);
          wg_fence();
          wgmma_rs_n128_t0(s, qa[0], qa[1], qa[2], qa[3], make_desc(kb, 2048, 128, 0), 0);
          wgmma_rs_n128_t0(s, qa[4], qa[5], qa[6], qa[7], make_desc(kb + 4096, 2048, 128, 0), 1);
          wg_commit();
          wg_wait<0>();
          reg_fence(s);
          reg_fence(O);
          if (tid == 0 && (step == 6 || step == 7)) PROF_T(28 + (step - 6) * 5);
          float mx0 = m0, mx1 = m1;
          #pragma unroll
          for (int b = 0; b < 8; b++) {
            if (b >= lo && b <= hi) {
              float* e = &s[8 * b];
              if (b == mblk) {
                e[0] = pa ? e[0] : -INFINITY; e[6] = pa ? e[6] : -INFINITY; e[1] = pb ? e[1] : -INFINITY; e[7] = pb ? e[7] : -INFINITY;
                e[2] = far ? -INFINITY : e[2]; e[3] = far ? -INFINITY : e[3]; e[4] = far ? e[4] : -INFINITY; e[5] = far ? e[5] : -INFINITY;
              }
              mx0 = fmaxf(mx0, fmaxf(fmaxf(e[0], e[1]), fmaxf(e[4], e[5])));
              mx1 = fmaxf(mx1, fmaxf(fmaxf(e[2], e[3]), fmaxf(e[6], e[7])));
            }
          }
          mx0 = quad_max(mx0); mx1 = quad_max(mx1);
          if (tid == 0 && (step == 6 || step == 7)) PROF_T(29 + (step - 6) * 5);
          const float c0 = ex2((m0 - mx0) * SM_SCALE), c1 = ex2((m1 - mx1) * SM_SCALE);
          m0 = mx0; m1 = mx1;
          const float n0 = -mx0 * SM_SCALE, n1 = -mx1 * SM_SCALE;
          #pragma unroll
          for (int i = 0; i < 3; i++) { O[4 * i] *= c0; O[4 * i + 1] *= c0; O[4 * i + 2] *= c1; O[4 * i + 3] *= c1; }
          uint32_t pf[8][4];
          #pragma unroll
          for (int b = 0; b < 8; b++) {
            if (b >= lo && b <= hi) {
              float e[8];
              #pragma unroll
              for (int u = 0; u < 8; u++) e[u] = ex2(fmaf(s[8 * b + u], SM_SCALE, (u & 2) ? n1 : n0));
              pf[b][0] = pack2(e[0], e[1]); pf[b][1] = pack2(e[2], e[3]); pf[b][2] = pack2(e[4], e[5]); pf[b][3] = pack2(e[6], e[7]);
            } else { pf[b][0] = pf[b][1] = pf[b][2] = pf[b][3] = 0u; }
          }
          reg_fence(O);
          if (tid == 0 && (step == 6 || step == 7)) PROF_T(30 + (step - 6) * 5);
          wg_fence();
          #pragma unroll
          for (int b = 0; b < 8; b++) wgmma_rs_n24_t1(O, pf[b][0], pf[b][1], pf[b][2], pf[b][3], make_desc(vb + b * 256, 128, 2048, 0), 1);
          wg_commit();
          if (tid == 0 && (step == 6 || step == 7)) PROF_T(31 + (step - 6) * 5);
        }
        if (step < 3) {
          wg_wait<0>();
          reg_fence(O);
          #pragma unroll
          for (int q = 0; q < 3; q++) if (h == q) {
            #pragma unroll
            for (int i = 0; i < 12; i++) sv[q][i] = O[i];
            sv[q][12] = m0; sv[q][13] = m1;
          }
        } else if (st == 2) {
          wg_wait<0>();
          reg_fence(O);
          const int src = (lane & 28) | (odd ? 0 : 2);
          const float i0 = rcp(__shfl_sync(~0u, odd ? O[0] : O[8], src)), i1 = rcp(__shfl_sync(~0u, odd ? O[2] : O[10], src));
          uint8_t* o = og + (5 * (h >> 1) + 2 * odd) * 2048;
          #pragma unroll
          for (int i = 0; i < 3; i++) {
            if (i == 1 || (i == 0 ? (!odd || !lowq) : (odd || lowq))) {
              *reinterpret_cast<uint32_t*>(o + i * 2048) = pack2(O[4 * i] * i0, O[4 * i + 1] * i0);
              *reinterpret_cast<uint32_t*>(o + i * 2048 + 128) = pack2(O[4 * i + 2] * i1, O[4 * i + 3] * i1);
            }
          }
        }
        if (step == 3 && tid == 0) PROF_T(4);
      }
      release_pair(B_ATTDONE);
      if (tid == 0) PROF_T(7);
      __syncwarp();
      if (lane == 0) red_release(&g_flags[FL_O + rbA * 8 + hq], 1u);
      if (tid == 0) PROF_T(8);
    }
    const int r0 = warp * 16 + g;
    const uint32_t stsm_row = (uint32_t)(warp * 16 + ((lane >> 3) & 1) * 8 + (lane & 7)) * 16 + (uint32_t)(lane >> 4) * 2048;
    uint32_t hr[10][2];
    {
      const __nv_bfloat16* xp = p.x + (size_t)(rbC * 128 + r0) * DM + 80 * j + 2 * c4;
      #pragma unroll
      for (int t = 0; t < 10; t++) { hr[t][0] = ldg_u32(xp + 8 * t); hr[t][1] = ldg_u32(xp + 8 * DM + 8 * t); }
      float acc[40];
      mbar_wait(bar(B_WOFULL), 0);
      #pragma unroll 1
      for (int t = 0; t < 8; t++) {
        const int s = t < 5 ? t : t - 5;
        mbar_wait(bar(B_CFULL + s), t >= 5);
        if (t == 6) mbar_wait(bar(B_WO4), 0);
        if (t == 0 && tid == 0) PROF_T(9);
        const uint32_t a = sb + s * OT_BYTES + wg * 1024;
        wg_fence();
        #pragma unroll
        for (int ks = 0; ks < 5; ks++) {
          const int k = 80 * t + 16 * ks;
          const uint32_t b = sb + (k >= 512 ? WO4_OFF : WO_OFF + (k >> 7) * 20480) + (k & 127) * 32;
          wgmma_ss_n80_t1(acc, make_desc(a + ks * 4096, 2048, 128, 0), make_desc(b, 4096, 256, 3), (t > 0 || ks > 0) ? 1 : 0);
        }
        wg_commit();
        wg_wait<1>();
        if (t >= 1 && t <= 3) release_pair(B_CEMPTY + t - 1);
      }
      wg_wait<0>();
      reg_fence(acc);
      release_pair(B_CDONE);
      if (tid == 0) PROF_T(10);
      named_sync(1, 256);
      float s0 = 0.f, q0 = 0.f, s1 = 0.f, q1 = 0.f;
      #pragma unroll
      for (int i = 0; i < 5; i++) {
        #pragma unroll
        for (int u = 0; u < 2; u++) {
          const int t = 2 * i + u;
          hr[t][0] = pack2(acc[4 * t] + bf_lo(hr[t][0]), acc[4 * t + 1] + bf_hi(hr[t][0]));
          hr[t][1] = pack2(acc[4 * t + 2] + bf_lo(hr[t][1]), acc[4 * t + 3] + bf_hi(hr[t][1]));
          const float a = bf_lo(hr[t][0]), b = bf_hi(hr[t][0]), c = bf_lo(hr[t][1]), d = bf_hi(hr[t][1]);
          s0 += a + b; q0 = fmaf(a, a, fmaf(b, b, q0)); s1 += c + d; q1 = fmaf(c, c, fmaf(d, d, q1));
        }
        stsm4(sb + i * 4096 + stsm_row, hr[2 * i][0], hr[2 * i][1], hr[2 * i + 1][0], hr[2 * i + 1][1]);
      }
      s0 = quad_sum(s0); q0 = quad_sum(q0); s1 = quad_sum(s1); q1 = quad_sum(q1);
      if (c4 == 0) { sts_f2(sb + 20480 + r0 * 8, s0, q0); sts_f2(sb + 20480 + (r0 + 8) * 8, s1, q1); }
      fence_async();
      __syncwarp();
      if (lane == 0) mbar_arrive(bar(B_HW));
      if (tid == 0) PROF_T(11);
    }
    {
      float acc[96];
      float hs0 = 0.f, hq0 = 0.f, hs1 = 0.f, hq1 = 0.f;
      #pragma unroll 1
      for (int t = 0; t < 8; t++) {
        const int s = t & 3;
        mbar_wait(bar(B_DBFULL + s), t >> 2);
        mbar_wait(bar(B_DAFULL + s), t >> 2);
        if (t == 0 && tid == 0) PROF_T(12);
        if (t == 2 && tid == 0) PROF_T(13);
        const uint32_t a = sb + s * HT_BYTES + wg * 1024, b = sb + DB_OFF + s * DB_SLOT;
        wg_fence();
        #pragma unroll
        for (int ks = 0; ks < 5; ks++)
          wgmma_ss_n192_t1(acc, make_desc(a + ks * 4096, 2048, 128, 0), make_desc(b + ks * 2048, 10240, 1024, 1), (t > 0 || ks > 0) ? 1 : 0);
        wg_commit();
        const float2 u0 = lds_f2(sb + s * HT_BYTES + 20480 + r0 * 8), u1 = lds_f2(sb + s * HT_BYTES + 20480 + (r0 + 8) * 8);
        hs0 += u0.x; hq0 += u0.y; hs1 += u1.x; hq1 += u1.y;
        wg_wait<1>();
        if (t > 0) { release_pair(B_DAEMPTY + ((t - 1) & 3)); if ((tid & 127) == 0) mbar_arrive(bar(B_DBEMPTY + ((t - 1) & 3))); }
      }
      wg_wait<0>();
      reg_fence(acc);
      if ((tid & 127) == 0) mbar_arrive(bar(B_DBEMPTY + 3));
      release_pair(B_DDONE);
      if (tid == 0) PROF_T(14);
      const float mu0 = hs0 * (1.f / DM), mu1 = hs1 * (1.f / DM);
      const float rs0 = rsq(fmaxf(hq0 * (1.f / DM) - mu0 * mu0, 0.f) + 1e-5f), rs1 = rsq(fmaxf(hq1 * (1.f / DM) - mu1 * mu1, 0.f) + 1e-5f);
      const float mr0 = -mu0 * rs0, mr1 = -mu1 * rs1;
      mbar_wait(bar(B_CS2), 0);
      named_sync(1, 256);
      #pragma unroll
      for (int i = 0; i < 12; i++) {
        uint32_t r[4];
        #pragma unroll
        for (int u = 0; u < 2; u++) {
          const int t = 2 * i + u;
          const float4 cb = lds_f4(sb + S_CS2 + (8 * t + 2 * c4) * 8);
          r[2 * u] = sq2(pack2_relu(fmaf(acc[4 * t], rs0, fmaf(cb.x, mr0, cb.y)), fmaf(acc[4 * t + 1], rs0, fmaf(cb.z, mr0, cb.w))));
          r[2 * u + 1] = sq2(pack2_relu(fmaf(acc[4 * t + 2], rs1, fmaf(cb.x, mr1, cb.y)), fmaf(acc[4 * t + 3], rs1, fmaf(cb.z, mr1, cb.w))));
        }
        stsm4(sb + rank * 49152 + i * 4096 + stsm_row, r[0], r[1], r[2], r[3]);
      }
      fence_async();
      __syncwarp();
      if (lane == 0) mbar_arrive(bar(B_FW));
      named_sync(2 + wg, 128);
      if (tid == 0) PROF_T(15);
    }
    {
      float acc1[96], acm[32], acr[32];
      const unsigned tag = lds_u32(sb + S_EPOCH);
      uint4* pbase = &g_part[(size_t)((rbC * 2 + rank) * 16) * (8 * 5 * 32) + warp * 160 + lane];
      unsigned* fbase = &g_flags[FL_P + ((rbC * 2 + rank) * 2 * 8 + warp) * 4];
      #pragma unroll 1
      for (int i = 0; i < 6; i++) {
        const int s = i % 5;
        mbar_wait(bar(B_EBFULL + s), i / 5);
        if (i >= 3) mbar_wait(bar(B_FFULL + i - 3), 0);
        const uint32_t a = sb + (i < 3 ? rank * 49152 + i * 16384 : (rank ^ 1) * 49152 + (i - 3) * 16384) + wg * 1024, b = sb + EB_OFF + s * EB_SLOT;
        wg_fence();
        #pragma unroll
        for (int ks = 0; ks < 4; ks++)
          wgmma_ss_n192_t1(acc1, make_desc(a + ks * 4096, 2048, 128, 0), make_desc(b + ks * 2048, 8192, 1024, 1), (i > 0 || ks > 0) ? 1 : 0);
        wg_commit();
        wg_wait<1>();
        if (i > 0 && (tid & 127) == 0) mbar_arrive(bar(B_EBEMPTY + (i - 1) % 5));
      }
      if (tid == 0) PROF_T(16);
      auto pass2_step = [&](int i) {
        const int s = i % 5;
        mbar_wait(bar(B_EBFULL + s), (i / 5) & 1);
        const int ks0 = i - 6;
        const uint32_t a = sb + (ks0 < 3 ? rank * 49152 + ks0 * 16384 : (rank ^ 1) * 49152 + (ks0 - 3) * 16384) + wg * 1024, b = sb + EB_OFF + s * EB_SLOT;
        wg_fence();
        #pragma unroll
        for (int ks = 0; ks < 4; ks++) {
          const int sc = (i > 6 || ks > 0) ? 1 : 0;
          wgmma_ss_n64_t1(acm, make_desc(a + ks * 4096, 2048, 128, 0), make_desc(b + ks * 2048, 8192, 1024, 1), sc);
          wgmma_ss_n64_t1(acr, make_desc(a + ks * 4096, 2048, 128, 0), make_desc(b + 8192 + ks * 512, 2048, 256, 3), sc);
        }
        wg_commit();
        wg_wait<1>();
        if ((tid & 127) == 0) mbar_arrive(bar(B_EBEMPTY + (i - 1) % 5));
      };
      pass2_step(6);
      {
        reg_fence(acc1);
        #pragma unroll
        for (int q = 0; q < 3; q++) {
          uint4* d = pbase + (((jj + 1 + q) & 3) * 4 + jj) * 1280;
          #pragma unroll
          for (int u = 0; u < 4; u++) {
            const float* a1 = &acc1[32 * q + 8 * u];
            d[u * 32] = make_uint4(pack2(a1[0], a1[1]), pack2(a1[2], a1[3]), pack2(a1[4], a1[5]), pack2(a1[6], a1[7]));
          }
        }
        __syncwarp();
        if (lane == 0) st_release(fbase + jj, tag);
      }
      #pragma unroll 1
      for (int i = 7; i < 12; i++) pass2_step(i);
      wg_wait<0>();
      reg_fence(acm); reg_fence(acr);
      if (tid == 0) PROF_T(17);
      #pragma unroll
      for (int q = 0; q < 3; q++) {
        const float* a1 = &acr[8 * q];
        pbase[(((jj + 1 + q) & 3) * 4 + jj) * 1280 + 128] = make_uint4(pack2(a1[0], a1[1]), pack2(a1[2], a1[3]), pack2(a1[4], a1[5]), pack2(a1[6], a1[7]));
      }
      __syncwarp();
      if (lane == 0) st_release(fbase + 32 + jj, tag);
      const __nv_bfloat16* b2p = p.b2 + 80 * j + 2 * c4;
      float k[40];
      #pragma unroll
      for (int t = 0; t < 10; t++) {
        const uint32_t bb = ldg_u32(b2p + 8 * t);
        const float* a1 = t < 8 ? &acm[4 * t] : &acr[24 + 4 * (t - 8)];
        k[4 * t] = a1[0] + bf_lo(bb) + bf_lo(hr[t][0]); k[4 * t + 1] = a1[1] + bf_hi(bb) + bf_hi(hr[t][0]);
        k[4 * t + 2] = a1[2] + bf_lo(bb) + bf_lo(hr[t][1]); k[4 * t + 3] = a1[3] + bf_hi(bb) + bf_hi(hr[t][1]);
      }
      __nv_bfloat16* op = p.out + (size_t)(rbC * 128 + r0) * DM + 80 * j + 2 * c4;
      #pragma unroll
      for (int pass = 0; pass < 2; pass++) {
        unsigned n = 0;
        while (true) {
          const unsigned v = ld_relaxed(fbase + pass * 32 + (lane & 3));
          if (__all_sync(~0u, (lane & 3) == jj || (int)(v - tag) >= 0)) break;
          spin_guard(n);
        }
        #pragma unroll
        for (int d = 1; d < 4; d++) {
          const uint4* src = pbase + (jj * 4 + ((jj + d) & 3)) * 1280;
          #pragma unroll
          for (int u = (pass ? 4 : 0); u < (pass ? 5 : 4); u++) {
            const uint4 v = ldg_cg_u4(src + u * 32);
            float* kk = &k[8 * u];
            kk[0] += bf_lo(v.x); kk[1] += bf_hi(v.x); kk[2] += bf_lo(v.y); kk[3] += bf_hi(v.y);
            kk[4] += bf_lo(v.z); kk[5] += bf_hi(v.z); kk[6] += bf_lo(v.w); kk[7] += bf_hi(v.w);
          }
        }
        #pragma unroll
        for (int t = (pass ? 8 : 0); t < (pass ? 10 : 8); t++) {
          *reinterpret_cast<uint32_t*>(op + 8 * t) = pack2(k[4 * t], k[4 * t + 1]);
          *reinterpret_cast<uint32_t*>(op + 8 * DM + 8 * t) = pack2(k[4 * t + 2], k[4 * t + 3]);
        }
      }
      if (tid == 0) PROF_T(18);
    }
  }
  __syncwarp();
  cluster_arrive();
  cluster_wait();
  if (tid == 0) PROF_T(19);
}

typedef CUresult (*EncodeTiledFn)(CUtensorMap*, CUtensorMapDataType, cuuint32_t, void*, const cuuint64_t*, const cuuint64_t*, const cuuint32_t*,
                                  const cuuint32_t*, CUtensorMapInterleave, CUtensorMapSwizzle, CUtensorMapL2promotion, CUtensorMapFloatOOBfill);

static bool encode_map(EncodeTiledFn fn, CUtensorMap* m, const void* ptr, int rank, const cuuint64_t* dims, const cuuint64_t* strides, const cuuint32_t* box,
                       CUtensorMapSwizzle sw) {
  const cuuint32_t es[3] = {1, 1, 1};
  return fn(m, CU_TENSOR_MAP_DATA_TYPE_BFLOAT16, rank, const_cast<void*>(ptr), dims, strides, box, es, CU_TENSOR_MAP_INTERLEAVE_NONE, sw,
            CU_TENSOR_MAP_L2_PROMOTION_L2_256B, CU_TENSOR_MAP_FLOAT_OOB_FILL_NONE) == CUDA_SUCCESS;
}

}

extern "C" void kernel_launch(void* const* d_in, const int* in_sizes, int n_in, void* d_out, int out_size) {
  using namespace blk;
  (void)in_sizes; (void)n_in; (void)out_size;
  static EncodeTiledFn encode = nullptr;
  if (!encode) {
    cudaDriverEntryPointQueryResult st;
    void* fn = nullptr;
    if (cudaGetDriverEntryPoint("cuTensorMapEncodeTiled", &fn, cudaEnableDefault, &st) != cudaSuccess || !fn) return;
    encode = reinterpret_cast<EncodeTiledFn>(fn);
    cudaFuncSetAttribute(fused_block_kernel, cudaFuncAttributeMaxDynamicSharedMemorySize, SMEM_BYTES);
  }
  Params p;
  p.x = static_cast<const __nv_bfloat16*>(d_in[0]); p.wqkv = static_cast<const __nv_bfloat16*>(d_in[1]); p.wo = static_cast<const __nv_bfloat16*>(d_in[2]);
  p.w1 = static_cast<const __nv_bfloat16*>(d_in[4]); p.b1 = static_cast<const __nv_bfloat16*>(d_in[5]);
  p.w2 = static_cast<const __nv_bfloat16*>(d_in[6]); p.b2 = static_cast<const __nv_bfloat16*>(d_in[7]); p.out = static_cast<__nv_bfloat16*>(d_out);
  CUtensorMap mX, mWq, mWr, mWo, mW1, mW2, mW2r;
  bool ok = true;
  { cuuint64_t d[2] = {DM, SEQ}, s[1] = {DM * 2}; cuuint32_t b[2] = {64, 128}; ok &= encode_map(encode, &mX, p.x, 2, d, s, b, CU_TENSOR_MAP_SWIZZLE_128B); }
  { cuuint64_t d[3] = {DM, DM, 3}, s[2] = {3 * DM * 2, DM * 2}; cuuint32_t b[3] = {64, 32, 3}; ok &= encode_map(encode, &mWq, p.wqkv, 3, d, s, b, CU_TENSOR_MAP_SWIZZLE_128B); }
  { cuuint64_t d[3] = {DM, DM, 3}, s[2] = {3 * DM * 2, DM * 2}; cuuint32_t b[3] = {16, 32, 3}; ok &= encode_map(encode, &mWr, p.wqkv, 3, d, s, b, CU_TENSOR_MAP_SWIZZLE_32B); }
  { cuuint64_t d[3] = {16, DM, DM / 16}, s[2] = {DM * 2, 32}; cuuint32_t b[3] = {16, 128, 5}; ok &= encode_map(encode, &mWo, p.wo, 3, d, s, b, CU_TENSOR_MAP_SWIZZLE_32B); }
  { cuuint64_t d[2] = {FF, DM}, s[1] = {FF * 2}; cuuint32_t b[2] = {64, 80}; ok &= encode_map(encode, &mW1, p.w1, 2, d, s, b, CU_TENSOR_MAP_SWIZZLE_128B); }
  { cuuint64_t d[2] = {DM, FF}, s[1] = {DM * 2}; cuuint32_t b[2] = {64, 64}; ok &= encode_map(encode, &mW2, p.w2, 2, d, s, b, CU_TENSOR_MAP_SWIZZLE_128B); }
  { cuuint64_t d[2] = {DM, FF}, s[1] = {DM * 2}; cuuint32_t b[2] = {16, 64}; ok &= encode_map(encode, &mW2r, p.w2, 2, d, s, b, CU_TENSOR_MAP_SWIZZLE_32B); }
  if (!ok) return;
  cudaLaunchConfig_t cfg = {};
  cfg.gridDim = dim3(NCTA); cfg.blockDim = dim3(384); cfg.dynamicSmemBytes = SMEM_BYTES; cfg.stream = cudaStreamPerThread;
  cudaLaunchAttribute at[1];
  at[0].id = cudaLaunchAttributeClusterDimension; at[0].val.clusterDim.x = 2; at[0].val.clusterDim.y = 1; at[0].val.clusterDim.z = 1;
  cfg.attrs = at; cfg.numAttrs = 1;
  cudaLaunchKernelEx(&cfg, fused_block_kernel, mX, mWq, mWr, mWo, mW1, mW2, mW2r, p);
}
```

```cpp
#include <cuda_runtime.h>
#include <cuda.h>
#include <cuda_bf16.h>
#include <stdint.h>

namespace blk {

constexpr int SEQ = 2048, DM = 640, FF = 1536;
constexpr int NCTA = 128;

constexpr uint32_t A_STAGE = 47104;
constexpr uint32_t CS_STG0 = 188416, CS_STG1 = 217088;
constexpr uint32_t KV_HALF = 22528, KV_BLK = 45056;
constexpr uint32_t KV_FAR = 0, KV_PREV = 45056, KV_OWN = 90112;
constexpr uint32_t WO_OFF = 135168, WO4_OFF = 102400;
constexpr uint32_t OT_BYTES = 20480;
constexpr uint32_t HT_BYTES = 21504;
constexpr uint32_t DB_OFF = 98304, DB_SLOT = 30720;
constexpr uint32_t EB_OFF = 98304, EB_SLOT = 24576;
constexpr uint32_t AUX = 225280;
constexpr uint32_t BARS = AUX;
constexpr uint32_t S_CS1 = AUX + 512;
constexpr uint32_t S_CS2 = AUX + 2560;
constexpr uint32_t S_EPOCH = AUX + 4096;
constexpr uint32_t S_PROF = AUX + 4096 + 64;
constexpr uint32_t SMEM_BYTES = S_PROF;

enum Bar : int {
  B_AFULL = 0  , B_AEMPTY = 4  ,
  B_STAT = 8, B_KVFULL = 9  , B_KVST = 13, B_AUXDONE = 14, B_WOFULL = 15, B_CFULL = 16  , B_WO4 = 21, B_DAFULL = 22  , B_DBFULL = 26  ,
  B_FFULL = 30  , B_EBFULL = 33  , B_CS2 = 38, B_EPOCH = 39, B_AUX2 = 40,
  B_DBEMPTY = 41  , B_EBEMPTY = 45  , B_KVW = 50  , B_HW = 52, B_FW = 53, B_DAEMPTY = 54  , B_ATTDONE = 58, B_CEMPTY = 59  ,
  B_CDONE = 62, B_DDONE = 63, B_COUNT = 64
};
__device__ __forceinline__ uint32_t bar_count(int i) { return i < B_DBEMPTY ? 1 : i < B_KVW ? 2 : i < B_DAEMPTY ? 8 : i == B_DAEMPTY ? 6 : 4; }

constexpr int FL_EPOCH = 0, FL_KV = 128, FL_O = 384, FL_H = 512, FL_P = 640;
struct Scratch {
  uint4 kv[128 * (KV_BLK / 16)];
  uint4 o[128 * (OT_BYTES / 16)];
  uint4 h[128 * (HT_BYTES / 16)];
  uint4 part[16 * 2 * 4 * 4 * 8 * 5 * 32];
  unsigned long long cs[3 * DM + FF];
  unsigned flags[640 + 16 * 2 * 2 * 8 * 4];
};
__device__ __align__(1024) Scratch g_scr;
#define PROF_T(i) do {} while (0)
#define PROF_S(k) do {} while (0)

__device__ __forceinline__ uint32_t smem_u32(const void* p) { return (uint32_t)__cvta_generic_to_shared(p); }
__device__ __forceinline__ void mbar_init(uint32_t bar, uint32_t cnt) { asm volatile("mbarrier.init.shared::cta.b64 [%0], %1;" :: "r"(bar), "r"(cnt)); }
__device__ __forceinline__ void mbar_expect_tx(uint32_t bar, uint32_t bytes) { asm volatile("mbarrier.arrive.expect_tx.shared::cta.b64 _, [%0], %1;" :: "r"(bar), "r"(bytes) : "memory"); }
__device__ __forceinline__ void mbar_arrive(uint32_t bar) { asm volatile("mbarrier.arrive.shared::cta.b64 _, [%0];" :: "r"(bar) : "memory"); }
__device__ __forceinline__ uint32_t mapa(uint32_t addr, uint32_t cta) { uint32_t r; asm volatile("mapa.shared::cluster.u32 %0, %1, %2;" : "=r"(r) : "r"(addr), "r"(cta)); return r; }
__device__ __forceinline__ void mbar_arrive_cluster(uint32_t bar, uint32_t cta) {
  asm volatile("{\n.reg .b32 ra;\nmapa.shared::cluster.u32 ra, %0, %1;\nmbarrier.arrive.shared::cluster.b64 _, [ra];\n}" :: "r"(bar), "r"(cta) : "memory");
}
constexpr unsigned SPIN_LIMIT = 1u << 22;
__device__ __forceinline__ void mbar_wait(uint32_t bar, uint32_t parity, unsigned& n) {
  asm volatile("{\n.reg .pred p, q;\nWAIT_%=:\nmbarrier.try_wait.parity.shared::cta.b64 p, [%1], %2;\n@!p add.u32 %0, %0, 1;\n"
               "setp.lt.and.u32 q, %0, %3, !p;\n@q bra WAIT_%=;\n}" : "+&r"(n) : "r"(bar), "r"(parity), "n"(SPIN_LIMIT) : "memory");
}
__device__ __forceinline__ unsigned ld_relaxed(const unsigned* p) { unsigned v; asm volatile("ld.relaxed.gpu.global.u32 %0, [%1];" : "=r"(v) : "l"(p) : "memory"); return v; }
__device__ __forceinline__ unsigned ld_acquire(const unsigned* p) { unsigned v; asm volatile("ld.acquire.gpu.global.u32 %0, [%1];" : "=r"(v) : "l"(p) : "memory"); return v; }
__device__ __forceinline__ unsigned long long ld_relaxed64(const unsigned long long* p) { unsigned long long v; asm volatile("ld.relaxed.gpu.global.u64 %0, [%1];" : "=l"(v) : "l"(p) : "memory"); return v; }
__device__ __forceinline__ void st_relaxed(unsigned* p, unsigned v) { asm volatile("st.relaxed.gpu.global.u32 [%0], %1;" :: "l"(p), "r"(v) : "memory"); }
__device__ __forceinline__ void st_relaxed64(unsigned long long* p, unsigned lo, unsigned hi) {
  asm volatile("{\n.reg .b64 v;\nmov.b64 v, {%1, %2};\nst.relaxed.gpu.global.u64 [%0], v;\n}" :: "l"(p), "r"(lo), "r"(hi) : "memory");
}
__device__ __forceinline__ void st_release(unsigned* p, unsigned v) { asm volatile("st.release.gpu.global.u32 [%0], %1;" :: "l"(p), "r"(v) : "memory"); }
__device__ __forceinline__ void red_release(unsigned* p, unsigned v) { asm volatile("red.release.gpu.global.add.u32 [%0], %1;" :: "l"(p), "r"(v) : "memory"); }
__device__ __forceinline__ void fence_acq() { asm volatile("fence.acq_rel.gpu;" ::: "memory"); }
__device__ __forceinline__ void fence_async() { asm volatile("fence.proxy.async.shared::cta;" ::: "memory"); }
__device__ __forceinline__ void fence_async_global() { asm volatile("fence.proxy.async.global;" ::: "memory"); }
__device__ __forceinline__ bool elect_one() {
  uint32_t r;
  asm volatile("{\n.reg .pred P;\nelect.sync _|P, 0xffffffff;\nselp.u32 %0, 1, 0, P;\n}" : "=r"(r));
  return r != 0;
}
__device__ __forceinline__ void wait_flag(const unsigned* p, unsigned target, unsigned& n) {
  while ((int)(ld_acquire(p) - target) < 0 && ++n < SPIN_LIMIT) {}
}
__device__ __forceinline__ void tma_2d(uint32_t dst, const CUtensorMap* map, int c0, int c1, uint32_t bar) {
  asm volatile("cp.async.bulk.tensor.2d.shared::cluster.global.mbarrier::complete_tx::bytes [%0], [%1, {%3, %4}], [%2];"
    :: "r"(dst), "l"(map), "r"(bar), "r"(c0), "r"(c1) : "memory");
}
__device__ __forceinline__ void tma_3d(uint32_t dst, const CUtensorMap* map, int c0, int c1, int c2, uint32_t bar) {
  asm volatile("cp.async.bulk.tensor.3d.shared::cluster.global.mbarrier::complete_tx::bytes [%0], [%1, {%3, %4, %5}], [%2];"
    :: "r"(dst), "l"(map), "r"(bar), "r"(c0), "r"(c1), "r"(c2) : "memory");
}
__device__ __forceinline__ void tma_3d_mc(uint32_t dst, const CUtensorMap* map, int c0, int c1, int c2, uint32_t bar) {
  asm volatile("cp.async.bulk.tensor.3d.shared::cluster.global.mbarrier::complete_tx::bytes.multicast::cluster [%0], [%1, {%3, %4, %5}], [%2], %6;"
    :: "r"(dst), "l"(map), "r"(bar), "r"(c0), "r"(c1), "r"(c2), "h"((uint16_t)3) : "memory");
}
__device__ __forceinline__ void bulk_ld(uint32_t dst, const void* src, uint32_t bytes, uint32_t bar) {
  asm volatile("cp.async.bulk.shared::cluster.global.mbarrier::complete_tx::bytes [%0], [%1], %2, [%3];" :: "r"(dst), "l"(src), "r"(bytes), "r"(bar) : "memory");
}
__device__ __forceinline__ void bulk_ld_mc(uint32_t dst, const void* src, uint32_t bytes, uint32_t bar) {
  asm volatile("cp.async.bulk.shared::cluster.global.mbarrier::complete_tx::bytes.multicast::cluster [%0], [%1], %2, [%3], %4;"
    :: "r"(dst), "l"(src), "r"(bytes), "r"(bar), "h"((uint16_t)3) : "memory");
}
__device__ __forceinline__ void bulk_st(void* dst, uint32_t src, uint32_t bytes) {
  asm volatile("cp.async.bulk.global.shared::cta.bulk_group [%0], [%1], %2;" :: "l"(dst), "r"(src), "r"(bytes) : "memory");
}
__device__ __forceinline__ void bulk_dsmem(uint32_t rdst, uint32_t src, uint32_t bytes, uint32_t rbar) {
  asm volatile("cp.async.bulk.shared::cluster.shared::cta.mbarrier::complete_tx::bytes [%0], [%1], %2, [%3];" :: "r"(rdst), "r"(src), "r"(bytes), "r"(rbar) : "memory");
}
__device__ __forceinline__ void bulk_commit() { asm volatile("cp.async.bulk.commit_group;" ::: "memory"); }
__device__ __forceinline__ void bulk_wait0() { asm volatile("cp.async.bulk.wait_group 0;" ::: "memory"); }
__device__ __forceinline__ void bulk_wait1() { asm volatile("cp.async.bulk.wait_group 1;" ::: "memory"); }
__device__ __forceinline__ void prefetch_l2(const void* p, uint32_t bytes) { asm volatile("cp.async.bulk.prefetch.L2.global [%0], %1;" :: "l"(p), "r"(bytes) : "memory"); }
__device__ __forceinline__ void prefetch_map(const CUtensorMap* m) { asm volatile("prefetch.tensormap [%0];" :: "l"(m) : "memory"); }
__device__ __forceinline__ void cp_async16(uint32_t dst, const void* src) { asm volatile("cp.async.cg.shared.global [%0], [%1], 16;" :: "r"(dst), "l"(src) : "memory"); }
__device__ __forceinline__ void cp_async_wait_all() { asm volatile("cp.async.wait_all;" ::: "memory"); }
__device__ __forceinline__ void cluster_arrive() { asm volatile("barrier.cluster.arrive.release.aligned;" ::: "memory"); }
__device__ __forceinline__ void cluster_wait() { asm volatile("barrier.cluster.wait.acquire.aligned;" ::: "memory"); }
__device__ __forceinline__ void named_sync(int id, int n) { asm volatile("bar.sync %0, %1;" :: "r"(id), "r"(n) : "memory"); }
__device__ __forceinline__ void wg_fence() { asm volatile("wgmma.fence.sync.aligned;" ::: "memory"); }
__device__ __forceinline__ void wg_commit() { asm volatile("wgmma.commit_group.sync.aligned;" ::: "memory"); }
template <int N> __device__ __forceinline__ void wg_wait() { asm volatile("wgmma.wait_group.sync.aligned %0;" :: "n"(N) : "memory"); }
template <int N> __device__ __forceinline__ void reg_fence(float (&d)[N]) {
  #pragma unroll
  for (int i = 0; i < N; i++) asm volatile("" : "+f"(d[i]) :: "memory");
}
__device__ __forceinline__ uint32_t desc_lo(uint32_t addr, uint32_t lbo) { return ((addr & 0x3FFFF) >> 4) | ((lbo >> 4) << 16); }
template <uint32_t SBO, uint32_t SWZ> __device__ __forceinline__ uint64_t desc(uint32_t lo, uint32_t byte_off) {
  return ((uint64_t)((SBO >> 4) | (SWZ << 30)) << 32) | (uint64_t)(lo + (byte_off >> 4));
}
__device__ __forceinline__ uint32_t pack2(float lo, float hi) { uint32_t r; asm("cvt.rn.bf16x2.f32 %0, %1, %2;" : "=r"(r) : "f"(hi), "f"(lo)); return r; }
__device__ __forceinline__ uint32_t pack2_relu(float lo, float hi) { uint32_t r; asm("cvt.rn.relu.bf16x2.f32 %0, %1, %2;" : "=r"(r) : "f"(hi), "f"(lo)); return r; }
__device__ __forceinline__ uint32_t sq2(uint32_t v) { uint32_t r; asm("mul.rn.bf16x2 %0, %1, %1;" : "=r"(r) : "r"(v)); return r; }
__device__ __forceinline__ float bf_lo(uint32_t v) { return __uint_as_float(v << 16); }
__device__ __forceinline__ float bf_hi(uint32_t v) { return __uint_as_float(v & 0xffff0000u); }
__device__ __forceinline__ float ex2(float x) { float r; asm("ex2.approx.ftz.f32 %0, %1;" : "=f"(r) : "f"(x)); return r; }
__device__ __forceinline__ float rcp(float x) { float r; asm("rcp.approx.ftz.f32 %0, %1;" : "=f"(r) : "f"(x)); return r; }
__device__ __forceinline__ float rsq(float x) { float r; asm("rsqrt.approx.ftz.f32 %0, %1;" : "=f"(r) : "f"(x)); return r; }
__device__ __forceinline__ void stsm4(uint32_t addr, uint32_t a, uint32_t b, uint32_t c, uint32_t d) {
  asm volatile("stmatrix.sync.aligned.m8n8.x4.shared.b16 [%0], {%1, %2, %3, %4};" :: "r"(addr), "r"(a), "r"(b), "r"(c), "r"(d) : "memory");
}
__device__ __forceinline__ void stsm2(uint32_t addr, uint32_t a, uint32_t b) {
  asm volatile("stmatrix.sync.aligned.m8n8.x2.shared.b16 [%0], {%1, %2};" :: "r"(addr), "r"(a), "r"(b) : "memory");
}
__device__ __forceinline__ void ldsm4(uint32_t addr, uint32_t (&r)[4]) {
  asm volatile("ldmatrix.sync.aligned.m8n8.x4.shared.b16 {%0, %1, %2, %3}, [%4];" : "=r"(r[0]), "=r"(r[1]), "=r"(r[2]), "=r"(r[3]) : "r"(addr) : "memory");
}
__device__ __forceinline__ float2 lds_f2(uint32_t a) { float2 v; asm volatile("ld.shared.v2.f32 {%0, %1}, [%2];" : "=f"(v.x), "=f"(v.y) : "r"(a)); return v; }
__device__ __forceinline__ float4 lds_f4(uint32_t a) { float4 v; asm volatile("ld.shared.v4.f32 {%0, %1, %2, %3}, [%4];" : "=f"(v.x), "=f"(v.y), "=f"(v.z), "=f"(v.w) : "r"(a)); return v; }
__device__ __forceinline__ uint4 lds_u4(uint32_t a) { uint4 v; asm volatile("ld.shared.v4.u32 {%0, %1, %2, %3}, [%4];" : "=r"(v.x), "=r"(v.y), "=r"(v.z), "=r"(v.w) : "r"(a)); return v; }
__device__ __forceinline__ void sts_f2(uint32_t a, float x, float y) { asm volatile("st.shared.v2.f32 [%0], {%1, %2};" :: "r"(a), "f"(x), "f"(y) : "memory"); }
__device__ __forceinline__ void sts_u32(uint32_t a, uint32_t x) { asm volatile("st.shared.u32 [%0], %1;" :: "r"(a), "r"(x) : "memory"); }
__device__ __forceinline__ uint32_t lds_u32(uint32_t a) { uint32_t v; asm volatile("ld.shared.u32 %0, [%1];" : "=r"(v) : "r"(a) : "memory"); return v; }
__device__ __forceinline__ uint32_t ldg_u32(const void* p) { uint32_t v; asm volatile("ld.global.nc.u32 %0, [%1];" : "=r"(v) : "l"(p)); return v; }
__device__ __forceinline__ uint4 ldg_cg_u4(const void* p) { uint4 v; asm volatile("ld.global.cg.v4.u32 {%0, %1, %2, %3}, [%4];" : "=r"(v.x), "=r"(v.y), "=r"(v.z), "=r"(v.w) : "l"(p) : "memory"); return v; }
__device__ __forceinline__ float quad_max(float v) { v = fmaxf(v, __shfl_xor_sync(~0u, v, 1)); return fmaxf(v, __shfl_xor_sync(~0u, v, 2)); }
__device__ __forceinline__ float quad_sum(float v) { v += __shfl_xor_sync(~0u, v, 1); return v + __shfl_xor_sync(~0u, v, 2); }

__device__ __forceinline__ void wgmma_rs_n192_t1(float (&d)[96], uint32_t a0, uint32_t a1, uint32_t a2, uint32_t a3, uint64_t db, int scale_d) {
  asm volatile("{\n.reg .pred p;\nsetp.ne.b32 p, %101, 0;\nwgmma.mma_async.sync.aligned.m64n192k16.f32.bf16.bf16 {%0, %1, %2, %3, %4, %5, %6, %7, %8, %9, %10, %11, %12, %13, %14, %15, %16, %17, %18, %19, %20, %21, %22, %23, %24, %25, %26, %27, %28, %29, %30, %31, %32, %33, %34, %35, %36, %37, %38, %39, %40, %41, %42, %43, %44, %45, %46, %47, %48, %49, %50, %51, %52, %53, %54, %55, %56, %57, %58, %59, %60, %61, %62, %63, %64, %65, %66, %67, %68, %69, %70, %71, %72, %73, %74, %75, %76, %77, %78, %79, %80, %81, %82, %83, %84, %85, %86, %87, %88, %89, %90, %91, %92, %93, %94, %95}, {%96, %97, %98, %99}, %100, p, 1, 1, 1;\n}"
    : "+f"(d[0]), "+f"(d[1]), "+f"(d[2]), "+f"(d[3]), "+f"(d[4]), "+f"(d[5]), "+f"(d[6]), "+f"(d[7]), "+f"(d[8]), "+f"(d[9]), "+f"(d[10]), "+f"(d[11]), "+f"(d[12]), "+f"(d[13]), "+f"(d[14]), "+f"(d[15]), "+f"(d[16]), "+f"(d[17]), "+f"(d[18]), "+f"(d[19]), "+f"(d[20]), "+f"(d[21]), "+f"(d[22]), "+f"(d[23]), "+f"(d[24]), "+f"(d[25]), "+f"(d[26]), "+f"(d[27]), "+f"(d[28]), "+f"(d[29]), "+f"(d[30]), "+f"(d[31]), "+f"(d[32]), "+f"(d[33]), "+f"(d[34]), "+f"(d[35]), "+f"(d[36]), "+f"(d[37]), "+f"(d[38]), "+f"(d[39]), "+f"(d[40]), "+f"(d[41]), "+f"(d[42]), "+f"(d[43]), "+f"(d[44]), "+f"(d[45]), "+f"(d[46]), "+f"(d[47]), "+f"(d[48]), "+f"(d[49]), "+f"(d[50]), "+f"(d[51]), "+f"(d[52]), "+f"(d[53]), "+f"(d[54]), "+f"(d[55]), "+f"(d[56]), "+f"(d[57]), "+f"(d[58]), "+f"(d[59]), "+f"(d[60]), "+f"(d[61]), "+f"(d[62]), "+f"(d[63]), "+f"(d[64]), "+f"(d[65]), "+f"(d[66]), "+f"(d[67]), "+f"(d[68]), "+f"(d[69]), "+f"(d[70]), "+f"(d[71]), "+f"(d[72]), "+f"(d[73]), "+f"(d[74]), "+f"(d[75]), "+f"(d[76]), "+f"(d[77]), "+f"(d[78]), "+f"(d[79]), "+f"(d[80]), "+f"(d[81]), "+f"(d[82]), "+f"(d[83]), "+f"(d[84]), "+f"(d[85]), "+f"(d[86]), "+f"(d[87]), "+f"(d[88]), "+f"(d[89]), "+f"(d[90]), "+f"(d[91]), "+f"(d[92]), "+f"(d[93]), "+f"(d[94]), "+f"(d[95])
    : "r"(a0), "r"(a1), "r"(a2), "r"(a3), "l"(db), "r"(scale_d));
}

__device__ __forceinline__ void wgmma_rs_n48_t1(float (&d)[24], uint32_t a0, uint32_t a1, uint32_t a2, uint32_t a3, uint64_t db, int scale_d) {
  asm volatile("{\n.reg .pred p;\nsetp.ne.b32 p, %29, 0;\nwgmma.mma_async.sync.aligned.m64n48k16.f32.bf16.bf16 {%0, %1, %2, %3, %4, %5, %6, %7, %8, %9, %10, %11, %12, %13, %14, %15, %16, %17, %18, %19, %20, %21, %22, %23}, {%24, %25, %26, %27}, %28, p, 1, 1, 1;\n}"
    : "+f"(d[0]), "+f"(d[1]), "+f"(d[2]), "+f"(d[3]), "+f"(d[4]), "+f"(d[5]), "+f"(d[6]), "+f"(d[7]), "+f"(d[8]), "+f"(d[9]), "+f"(d[10]), "+f"(d[11]), "+f"(d[12]), "+f"(d[13]), "+f"(d[14]), "+f"(d[15]), "+f"(d[16]), "+f"(d[17]), "+f"(d[18]), "+f"(d[19]), "+f"(d[20]), "+f"(d[21]), "+f"(d[22]), "+f"(d[23])
    : "r"(a0), "r"(a1), "r"(a2), "r"(a3), "l"(db), "r"(scale_d));
}

__device__ __forceinline__ void wgmma_rs_n64_t0(float (&d)[32], uint32_t a0, uint32_t a1, uint32_t a2, uint32_t a3, uint64_t db, int scale_d) {
  asm volatile("{\n.reg .pred p;\nsetp.ne.b32 p, %37, 0;\nwgmma.mma_async.sync.aligned.m64n64k16.f32.bf16.bf16 {%0, %1, %2, %3, %4, %5, %6, %7, %8, %9, %10, %11, %12, %13, %14, %15, %16, %17, %18, %19, %20, %21, %22, %23, %24, %25, %26, %27, %28, %29, %30, %31}, {%32, %33, %34, %35}, %36, p, 1, 1, 0;\n}"
    : "+f"(d[0]), "+f"(d[1]), "+f"(d[2]), "+f"(d[3]), "+f"(d[4]), "+f"(d[5]), "+f"(d[6]), "+f"(d[7]), "+f"(d[8]), "+f"(d[9]), "+f"(d[10]), "+f"(d[11]), "+f"(d[12]), "+f"(d[13]), "+f"(d[14]), "+f"(d[15]), "+f"(d[16]), "+f"(d[17]), "+f"(d[18]), "+f"(d[19]), "+f"(d[20]), "+f"(d[21]), "+f"(d[22]), "+f"(d[23]), "+f"(d[24]), "+f"(d[25]), "+f"(d[26]), "+f"(d[27]), "+f"(d[28]), "+f"(d[29]), "+f"(d[30]), "+f"(d[31])
    : "r"(a0), "r"(a1), "r"(a2), "r"(a3), "l"(db), "r"(scale_d));
}

__device__ __forceinline__ void wgmma_rs_n24_t1(float (&d)[12], uint32_t a0, uint32_t a1, uint32_t a2, uint32_t a3, uint64_t db, int scale_d) {
  asm volatile("{\n.reg .pred p;\nsetp.ne.b32 p, %17, 0;\nwgmma.mma_async.sync.aligned.m64n24k16.f32.bf16.bf16 {%0, %1, %2, %3, %4, %5, %6, %7, %8, %9, %10, %11}, {%12, %13, %14, %15}, %16, p, 1, 1, 1;\n}"
    : "+f"(d[0]), "+f"(d[1]), "+f"(d[2]), "+f"(d[3]), "+f"(d[4]), "+f"(d[5]), "+f"(d[6]), "+f"(d[7]), "+f"(d[8]), "+f"(d[9]), "+f"(d[10]), "+f"(d[11])
    : "r"(a0), "r"(a1), "r"(a2), "r"(a3), "l"(db), "r"(scale_d));
}

__device__ __forceinline__ void wgmma_ss_n80_t1(float (&d)[40], uint64_t da, uint64_t db, int scale_d) {
  asm volatile("{\n.reg .pred p;\nsetp.ne.b32 p, %42, 0;\nwgmma.mma_async.sync.aligned.m64n80k16.f32.bf16.bf16 {%0, %1, %2, %3, %4, %5, %6, %7, %8, %9, %10, %11, %12, %13, %14, %15, %16, %17, %18, %19, %20, %21, %22, %23, %24, %25, %26, %27, %28, %29, %30, %31, %32, %33, %34, %35, %36, %37, %38, %39}, %40, %41, p, 1, 1, 0, 1;\n}"
    : "+f"(d[0]), "+f"(d[1]), "+f"(d[2]), "+f"(d[3]), "+f"(d[4]), "+f"(d[5]), "+f"(d[6]), "+f"(d[7]), "+f"(d[8]), "+f"(d[9]), "+f"(d[10]), "+f"(d[11]), "+f"(d[12]), "+f"(d[13]), "+f"(d[14]), "+f"(d[15]), "+f"(d[16]), "+f"(d[17]), "+f"(d[18]), "+f"(d[19]), "+f"(d[20]), "+f"(d[21]), "+f"(d[22]), "+f"(d[23]), "+f"(d[24]), "+f"(d[25]), "+f"(d[26]), "+f"(d[27]), "+f"(d[28]), "+f"(d[29]), "+f"(d[30]), "+f"(d[31]), "+f"(d[32]), "+f"(d[33]), "+f"(d[34]), "+f"(d[35]), "+f"(d[36]), "+f"(d[37]), "+f"(d[38]), "+f"(d[39])
    : "l"(da), "l"(db), "r"(scale_d));
}

__device__ __forceinline__ void wgmma_ss_n192_t1(float (&d)[96], uint64_t da, uint64_t db, int scale_d) {
  asm volatile("{\n.reg .pred p;\nsetp.ne.b32 p, %98, 0;\nwgmma.mma_async.sync.aligned.m64n192k16.f32.bf16.bf16 {%0, %1, %2, %3, %4, %5, %6, %7, %8, %9, %10, %11, %12, %13, %14, %15, %16, %17, %18, %19, %20, %21, %22, %23, %24, %25, %26, %27, %28, %29, %30, %31, %32, %33, %34, %35, %36, %37, %38, %39, %40, %41, %42, %43, %44, %45, %46, %47, %48, %49, %50, %51, %52, %53, %54, %55, %56, %57, %58, %59, %60, %61, %62, %63, %64, %65, %66, %67, %68, %69, %70, %71, %72, %73, %74, %75, %76, %77, %78, %79, %80, %81, %82, %83, %84, %85, %86, %87, %88, %89, %90, %91, %92, %93, %94, %95}, %96, %97, p, 1, 1, 0, 1;\n}"
    : "+f"(d[0]), "+f"(d[1]), "+f"(d[2]), "+f"(d[3]), "+f"(d[4]), "+f"(d[5]), "+f"(d[6]), "+f"(d[7]), "+f"(d[8]), "+f"(d[9]), "+f"(d[10]), "+f"(d[11]), "+f"(d[12]), "+f"(d[13]), "+f"(d[14]), "+f"(d[15]), "+f"(d[16]), "+f"(d[17]), "+f"(d[18]), "+f"(d[19]), "+f"(d[20]), "+f"(d[21]), "+f"(d[22]), "+f"(d[23]), "+f"(d[24]), "+f"(d[25]), "+f"(d[26]), "+f"(d[27]), "+f"(d[28]), "+f"(d[29]), "+f"(d[30]), "+f"(d[31]), "+f"(d[32]), "+f"(d[33]), "+f"(d[34]), "+f"(d[35]), "+f"(d[36]), "+f"(d[37]), "+f"(d[38]), "+f"(d[39]), "+f"(d[40]), "+f"(d[41]), "+f"(d[42]), "+f"(d[43]), "+f"(d[44]), "+f"(d[45]), "+f"(d[46]), "+f"(d[47]), "+f"(d[48]), "+f"(d[49]), "+f"(d[50]), "+f"(d[51]), "+f"(d[52]), "+f"(d[53]), "+f"(d[54]), "+f"(d[55]), "+f"(d[56]), "+f"(d[57]), "+f"(d[58]), "+f"(d[59]), "+f"(d[60]), "+f"(d[61]), "+f"(d[62]), "+f"(d[63]), "+f"(d[64]), "+f"(d[65]), "+f"(d[66]), "+f"(d[67]), "+f"(d[68]), "+f"(d[69]), "+f"(d[70]), "+f"(d[71]), "+f"(d[72]), "+f"(d[73]), "+f"(d[74]), "+f"(d[75]), "+f"(d[76]), "+f"(d[77]), "+f"(d[78]), "+f"(d[79]), "+f"(d[80]), "+f"(d[81]), "+f"(d[82]), "+f"(d[83]), "+f"(d[84]), "+f"(d[85]), "+f"(d[86]), "+f"(d[87]), "+f"(d[88]), "+f"(d[89]), "+f"(d[90]), "+f"(d[91]), "+f"(d[92]), "+f"(d[93]), "+f"(d[94]), "+f"(d[95])
    : "l"(da), "l"(db), "r"(scale_d));
}

__device__ __forceinline__ void wgmma_ss_n64_t1(float (&d)[32], uint64_t da, uint64_t db, int scale_d) {
  asm volatile("{\n.reg .pred p;\nsetp.ne.b32 p, %34, 0;\nwgmma.mma_async.sync.aligned.m64n64k16.f32.bf16.bf16 {%0, %1, %2, %3, %4, %5, %6, %7, %8, %9, %10, %11, %12, %13, %14, %15, %16, %17, %18, %19, %20, %21, %22, %23, %24, %25, %26, %27, %28, %29, %30, %31}, %32, %33, p, 1, 1, 0, 1;\n}"
    : "+f"(d[0]), "+f"(d[1]), "+f"(d[2]), "+f"(d[3]), "+f"(d[4]), "+f"(d[5]), "+f"(d[6]), "+f"(d[7]), "+f"(d[8]), "+f"(d[9]), "+f"(d[10]), "+f"(d[11]), "+f"(d[12]), "+f"(d[13]), "+f"(d[14]), "+f"(d[15]), "+f"(d[16]), "+f"(d[17]), "+f"(d[18]), "+f"(d[19]), "+f"(d[20]), "+f"(d[21]), "+f"(d[22]), "+f"(d[23]), "+f"(d[24]), "+f"(d[25]), "+f"(d[26]), "+f"(d[27]), "+f"(d[28]), "+f"(d[29]), "+f"(d[30]), "+f"(d[31])
    : "l"(da), "l"(db), "r"(scale_d));
}

struct Params {
  const __nv_bfloat16* x; const __nv_bfloat16* wqkv; const __nv_bfloat16* wo; const __nv_bfloat16* w1;
  const __nv_bfloat16* b1; const __nv_bfloat16* w2; const __nv_bfloat16* b2; __nv_bfloat16* out; Scratch* scr;
  uint2 unit[2][24];
};
enum : uint32_t { U_MASK = 4, U_HSHIFT = 3, U_FIRST = 32, U_WSHIFT = 6, U_WAIT = 256, U_EXISTS = 512, U_SAVEM = 1024 };
constexpr float SM_SCALE = 0.22360679774997896f * 1.4426950408889634f;

__global__ void __launch_bounds__(384, 1)
fused_block_kernel(const __grid_constant__ CUtensorMap mX, const __grid_constant__ CUtensorMap mWq, const __grid_constant__ CUtensorMap mWr,
                   const __grid_constant__ CUtensorMap mWo, const __grid_constant__ CUtensorMap mW1, const __grid_constant__ CUtensorMap mW2,
                   const __grid_constant__ CUtensorMap mW2r, const __grid_constant__ Params p) {
  extern __shared__ __align__(1024) uint8_t smem_raw[];
  const uint32_t sb = smem_u32(smem_raw);
  const int tid = threadIdx.x, lane = tid & 31;
  const int warp = __shfl_sync(~0u, tid >> 5, 0);
  const int cta = blockIdx.x, rank = cta & 1, pair = cta >> 1;
  const int hq = pair & 7, rbA = (pair >> 3) * 2 + rank;
  const int rbC = pair >> 2, jj = pair & 3, j = jj * 2 + rank;
  const uint32_t bars = sb + BARS;
  auto bar = [&](int i) { return bars + i * 8; };
  unsigned nspin = 0;

  if (warp == 8) {
    if (elect_one()) {
      PROF_T(0);
      prefetch_map(&mX); prefetch_map(&mWq); prefetch_map(&mWr);
      #pragma unroll
      for (int i = 0; i < 4; i++) { mbar_init(bar(B_AFULL + i), 1); mbar_init(bar(B_AEMPTY + i), 4); }
      asm volatile("fence.mbarrier_init.release.cluster;" ::: "memory");
      fence_async();
      #pragma unroll 1
      for (int it = 0; it < 4; it++) { mbar_expect_tx(bar(B_AFULL + it), A_STAGE); tma_2d(sb + it * A_STAGE, &mX, it * 64, rbA * 128, bar(B_AFULL + it)); }
    }
    __syncwarp();
  }
  asm volatile("barrier.cluster.arrive.relaxed.aligned;" ::: "memory");
  if (warp != 8 && elect_one()) {
    #pragma unroll 1
    for (int i = 8 + (warp < 8 ? warp : warp - 1); i < B_COUNT; i += 11) mbar_init(bar(i), bar_count(i));
    asm volatile("fence.mbarrier_init.release.cluster;" ::: "memory");
  }
  __syncwarp();
  cluster_wait();
  auto w_loads = [&](int it) {
    const uint32_t full = bar(B_AFULL + (it & 3)), dst = sb + (it & 3) * A_STAGE + 16384 + rank * 15360;
    tma_3d_mc(dst, &mWq, 80 * hq, it * 64 + 32 * rank, 0, full);
    tma_3d_mc(dst + 12288, &mWr, 80 * hq + 64, it * 64 + 32 * rank, 0, full);
  };
  if (warp == 8 && elect_one()) {
    #pragma unroll 1
    for (int it = 0; it < 4; it++) w_loads(it);
    PROF_T(27);
  }
  __syncthreads();

  if (warp >= 8) {
    asm volatile("setmaxnreg.dec.sync.aligned.u32 56;");
    if (warp == 11) {
      const unsigned tag = ld_relaxed(&p.scr->flags[FL_EPOCH + cta]) + 1u;
      #pragma unroll 1
      for (int job = 0; job < 2; job++) {
        if (job) mbar_wait(bar(B_KVW), 0, nspin);
        if (cta < (job ? 96 : 120)) {
          const int ld = job ? FF : 3 * DM, batch = job ? 16 : 40;
          const __nv_bfloat16* src = (job ? p.w1 : p.wqkv) + (size_t)(lane >> 1) * ld + cta * 16 + (lane & 1) * 8;
          const uint32_t sl = sb + (job ? CS_STG1 : CS_STG0) + lane * 16;
          float acc[8];
          #pragma unroll
          for (int i = 0; i < 8; i++) acc[i] = 0.f;
          #pragma unroll 1
          for (int r0 = 0; r0 < 40; r0 += batch) {
            const int n = 40 - r0 < batch ? 40 - r0 : batch;
            #pragma unroll 1
            for (int i = 0; i < n; i++) { cp_async16(sl + i * 512, src); src += 16 * ld; }
            cp_async_wait_all();
            #pragma unroll 1
            for (int i = 0; i < n; i++) {
              const uint4 v = lds_u4(sl + i * 512);
              acc[0] += bf_lo(v.x); acc[1] += bf_hi(v.x); acc[2] += bf_lo(v.y); acc[3] += bf_hi(v.y);
              acc[4] += bf_lo(v.z); acc[5] += bf_hi(v.z); acc[6] += bf_lo(v.w); acc[7] += bf_hi(v.w);
            }
          }
          #pragma unroll
          for (int o = 0; o < 3; o++) {
            const bool up = (lane >> (o + 1)) & 1;
            #pragma unroll
            for (int i = 0; i < (4 >> o); i++) {
              const float keep = up ? acc[2 * i + 1] : acc[2 * i], give = up ? acc[2 * i] : acc[2 * i + 1];
              acc[i] = keep + __shfl_xor_sync(~0u, give, 2 << o);
            }
          }
          const float v = acc[0] + __shfl_xor_sync(~0u, acc[0], 16);
          if (lane < 16) st_relaxed64(&p.scr->cs[(job ? 3 * DM : 0) + cta * 16 + (lane & 1) * 8 + (lane >> 1)], __float_as_uint(v), tag);
        }
        __syncwarp();
        if (elect_one()) {
          mbar_arrive(bar(job ? B_AUX2 : B_AUXDONE));
          if (job == 0) {
            st_relaxed(&p.scr->flags[FL_EPOCH + cta], tag);
            sts_u32(sb + S_EPOCH, tag);
            mbar_arrive(bar(B_EPOCH));
            PROF_T(26);
            prefetch_l2(reinterpret_cast<const uint8_t*>(p.wo) + cta * 6400, 6400);
            prefetch_l2(reinterpret_cast<const uint8_t*>(p.w1) + cta * 15360, 15360);
            prefetch_l2(reinterpret_cast<const uint8_t*>(p.w2) + cta * 15360, 15360);
          }
        }
        __syncwarp();
        const int n = job ? 96 : 120;
        const uint32_t dst = sb + (job ? S_CS2 : S_CS1);
        const uint4* csrc = reinterpret_cast<const uint4*>(job ? &p.scr->cs[3 * DM + 192 * j] : &p.scr->cs[80 * hq]);
        bool ok;
        do {
          #pragma unroll 1
          for (int c = lane; c < n; c += 32) cp_async16(dst + c * 16, csrc + c + (job ? 0 : (c >= 40 ? 280 : 0) + (c >= 80 ? 280 : 0)));
          cp_async_wait_all();
          ok = true;
          #pragma unroll 1
          for (int c = lane; c < n; c += 32) { const uint4 v = lds_u4(dst + c * 16); ok = ok && v.y == tag && v.w == tag; }
          ok = __all_sync(~0u, ok);
        } while (!ok && ++nspin < SPIN_LIMIT);
        if (job) {
          #pragma unroll 1
          for (int c = lane; c < 96; c += 32) {
            const uint32_t bb = ldg_u32(p.b1 + 192 * j + 2 * c);
            sts_u32(dst + c * 16 + 4, bb << 16); sts_u32(dst + c * 16 + 12, bb & 0xffff0000u);
          }
        }
        __syncwarp();
        if (lane == 0) { mbar_arrive(bar(job ? B_CS2 : B_STAT)); if (job == 0) PROF_T(23); }
      }
    } else if (warp == 10) {
      mbar_wait(bar(B_EPOCH), 0, nspin);
      const unsigned tag = lds_u32(sb + S_EPOCH);
      if (elect_one()) {
        uint4* kvg = &p.scr->kv[(rbA * 8 + hq) * (KV_BLK / 16)];
        unsigned* kvf = &p.scr->flags[FL_KV + (rbA * 8 + hq) * 2];
        mbar_wait(bar(B_KVW), 0, nspin);
        bulk_st(kvg + KV_HALF / 16, sb + KV_OWN + KV_HALF, KV_HALF);
        bulk_commit();
        mbar_wait(bar(B_KVW + 1), 0, nspin);
        bulk_st(kvg, sb + KV_OWN, KV_HALF);
        bulk_commit();
        bulk_wait1(); fence_async_global(); st_release(kvf, tag);
        PROF_T(28);
        bulk_wait0(); fence_async_global(); st_release(kvf + 1, tag);
        mbar_arrive(bar(B_KVST));
        PROF_T(24);
        mbar_wait(bar(B_HW), 0, nspin);
        mbar_arrive(bar(B_DAFULL + 0));
        bulk_st(&p.scr->h[(rbC * 8 + j) * (HT_BYTES / 16)], sb, HT_BYTES);
        bulk_commit();
        mbar_wait(bar(B_CDONE), 0, nspin);
        bulk_dsmem(mapa(sb + HT_BYTES, rank ^ 1), sb, HT_BYTES, mapa(bar(B_DAFULL + 1), rank ^ 1));
        bulk_wait0();
        fence_async_global();
        st_release(&p.scr->flags[FL_H + rbC * 8 + j], tag);
        mbar_arrive_cluster(bar(B_DAEMPTY + 0), 0); mbar_arrive_cluster(bar(B_DAEMPTY + 0), 1);
        PROF_T(25);
        mbar_wait(bar(B_FW), 0, nspin); mbar_wait(bar(B_DDONE), 0, nspin);
        #pragma unroll 1
        for (int i = 0; i < 3; i++) {
          const uint32_t off = rank * 49152 + i * 16384;
          bulk_dsmem(mapa(sb + off, rank ^ 1), sb + off, 16384, mapa(bar(B_FFULL + i), rank ^ 1));
        }
      }
    } else if (warp == 9) {
      mbar_wait(bar(B_EPOCH), 0, nspin);
      const unsigned tag = lds_u32(sb + S_EPOCH);
      if (elect_one()) {
        mbar_wait(bar(B_KVW), 0, nspin);
        #pragma unroll 1
        for (int c = 0; c < 4; c++) {
          const int d = 1 + (c & 1), blk = (rbA - d) * 8 + hq;
          const uint32_t off = c < 2 ? KV_HALF : 0;
          if (rbA >= d) {
            wait_flag(&p.scr->flags[FL_KV + blk * 2 + (c >> 1)], tag, nspin);
            fence_async_global();
            mbar_expect_tx(bar(B_KVFULL + c), KV_HALF);
            bulk_ld(sb + (d == 1 ? KV_PREV : KV_FAR) + off, reinterpret_cast<const uint8_t*>(p.scr->kv) + blk * KV_BLK + off, KV_HALF, bar(B_KVFULL + c));
          }
        }
        mbar_wait(bar(B_KVST), 0, nspin);
        mbar_wait(bar(B_AUXDONE), 0, nspin);
        mbar_expect_tx(bar(B_WOFULL), 81920);
        #pragma unroll 1
        for (int kb = 0; kb < 4; kb++) tma_3d(sb + WO_OFF + kb * 20480, &mWo, 0, kb * 128, 5 * j, bar(B_WOFULL));
        PROF_T(20);
      }
      #pragma unroll 1
      for (int job = 0; job < 2; job++) {
        const uint32_t bytes = job ? HT_BYTES : OT_BYTES, half = bytes >> 1;
        if (elect_one()) {
          if (job == 0) {
            mbar_wait(bar(B_ATTDONE), 0, nspin);
            mbar_expect_tx(bar(B_WO4), 20480);
            tma_3d(sb + WO4_OFF, &mWo, 0, 512, 5 * j, bar(B_WO4));
          }
          else {
            mbar_expect_tx(bar(B_DAFULL + 1), HT_BYTES);
            #pragma unroll 1
            for (int i = 0; i < 3; i++) mbar_expect_tx(bar(B_FFULL + i), 16384);
            mbar_wait(bar(B_CDONE), 0, nspin);
          }
        }
        __syncwarp();
        const unsigned* fl = &p.scr->flags[(job ? FL_H : FL_O) + rbC * 8 + (lane & 7)];
        const uint8_t* src = (job ? reinterpret_cast<const uint8_t*>(p.scr->h) : reinterpret_cast<const uint8_t*>(p.scr->o)) + rbC * 8 * bytes + rank * half;
        const unsigned target = job ? tag : tag * 8u;
        int next = job * 2;
        while (next < 8 && ++nspin < SPIN_LIMIT) {
          const unsigned ready = __ballot_sync(~0u, (int)(ld_acquire(fl) - target) >= 0);
          bool first = true;
          while (next < 8) {
            const int kt = job ? ((jj + (next >> 1)) & 3) * 2 + (next & 1) : next;
            if (!((ready >> kt) & 1)) break;
            if (elect_one()) {
              if (first) fence_async_global();
              const int s = job ? next & 3 : next < 5 ? next : next - 5;
              if (next >= (job ? 4 : 5)) mbar_wait(bar((job ? B_DAEMPTY : B_CEMPTY) + s), 0, nspin);
              if (job && next == 4) mbar_wait(bar(B_DAEMPTY + 1), 0, nspin);
              const uint32_t full = bar((job ? B_DAFULL : B_CFULL) + s);
              mbar_expect_tx(full, bytes);
              bulk_ld_mc(sb + s * bytes + rank * half, src + kt * bytes, half, full);
            }
            first = false;
            next++;
          }
        }
        if (lane == 0) PROF_T(21 + job);
      }
    } else {
      if (elect_one()) {
        #pragma unroll 1
        for (int it = 4; it < 10; it++) {
          const int s = it & 3;
          mbar_wait(bar(B_AEMPTY + s), ((it >> 2) - 1) & 1, nspin);
          mbar_expect_tx(bar(B_AFULL + s), A_STAGE);
          tma_2d(sb + s * A_STAGE, &mX, it * 64, rbA * 128, bar(B_AFULL + s));
          w_loads(it);
        }
        prefetch_map(&mWo); prefetch_map(&mW1); prefetch_map(&mW2); prefetch_map(&mW2r);
        mbar_wait(bar(B_AUX2), 0, nspin);
        mbar_wait(bar(B_CDONE), 0, nspin);
        #pragma unroll 1
        for (int t = 0; t < 8; t++) {
          const int s = t & 3;
          if (t >= 4) mbar_wait(bar(B_DBEMPTY + s), 0, nspin);
          const int kt = t < 2 ? (j ^ t) : (((jj + (t >> 1)) & 3) * 2 + (t & 1));
          const uint32_t full = bar(B_DBFULL + s), dst = sb + DB_OFF + s * DB_SLOT;
          mbar_expect_tx(full, 30720);
          #pragma unroll 1
          for (int c = 0; c < 3; c++) tma_2d(dst + c * 10240, &mW1, 192 * j + 64 * c, 80 * kt, full);
        }
        #pragma unroll 1
        for (int i = 0; i < 12; i++) {
          const int s = i < 5 ? i : i < 10 ? i - 5 : i - 10, ks = i < 6 ? i : i - 6;
          mbar_wait(bar(i < 4 ? B_DBEMPTY + i : B_EBEMPTY + s), i < 4 ? 1 : i >= 10 ? 1 : i >= 5 ? 0 : 1, nspin);
          const int krow = 384 * jj + (ks < 3 ? 192 * rank + 64 * ks : 192 * (rank ^ 1) + 64 * (ks - 3));
          const uint32_t full = bar(B_EBFULL + s), dst = sb + EB_OFF + s * EB_SLOT;
          mbar_expect_tx(full, i < 6 ? 24576 : 16384);
          #pragma unroll 1
          for (int c = 0; c < (i < 6 ? 3 : 1); c++) tma_2d(dst + c * 8192, &mW2, 160 * ((jj + (i < 6 ? 1 + c : 0)) & 3) + 80 * rank, krow, full);
          if (i >= 6) {
            #pragma unroll 1
            for (int c = 0; c < 4; c++) tma_2d(dst + 8192 + c * 2048, &mW2r, 160 * ((jj + 1 + c) & 3) + 80 * rank + 64, krow, full);
          }
        }
      }
    }
  } else {
    asm volatile("setmaxnreg.inc.sync.aligned.u32 224;");
    const int wg = warp >> 2, g = lane >> 2, c4 = lane & 3;
    auto release_pair = [&](int b) { if ((tid & 127) < 2) mbar_arrive_cluster(bar(b), tid & 1); };
    const int rbw = warp < 4 ? warp : 11 - warp;
    uint32_t qf[10][2];
    {
      float acc[96], acr[24];
      float sx0 = 0.f, sq0 = 0.f, sx1 = 0.f, sq1 = 0.f;
      const uint32_t arow = rbw * 16 + (lane & 7) + ((lane >> 3) & 1) * 8;
      const uint32_t aoff = sb + arow * 128 + (((lane >> 4) ^ (arow & 7)) << 4);
      const uint32_t lo192 = desc_lo(sb + 16384, 4096), lo48 = desc_lo(sb + 16384 + 12288, 1024);
      #pragma unroll 1
      for (int it = 0; it < 10; it++) {
        const int s = it & 3;
        mbar_wait(bar(B_AFULL + s), (it >> 2) & 1, nspin);
        if (it == 0 && tid == 0) PROF_T(1);
        const uint32_t so = s * A_STAGE;
        uint32_t af[4][4];
        #pragma unroll
        for (int kk = 0; kk < 4; kk++) ldsm4((aoff ^ (kk * 32)) + so, af[kk]);
        wg_fence();
        #pragma unroll
        for (int kk = 0; kk < 4; kk++) {
          const int sc = (it > 0 || kk > 0) ? 1 : 0;
          wgmma_rs_n192_t1(acc, af[kk][0], af[kk][1], af[kk][2], af[kk][3], desc<1024, 1>(lo192 + (so >> 4), (kk >> 1) * 15360 + (kk & 1) * 2048), sc);
          wgmma_rs_n48_t1(acr, af[kk][0], af[kk][1], af[kk][2], af[kk][3], desc<256, 3>(lo48 + (so >> 4), (kk >> 1) * 15360 + (kk & 1) * 512), sc);
        }
        wg_commit();
        #pragma unroll
        for (int kk = 0; kk < 4; kk++) {
          #pragma unroll
          for (int u = 0; u < 4; u++) {
            const float lo = bf_lo(af[kk][u]), hi = bf_hi(af[kk][u]);
            if (u & 1) { sx1 += lo + hi; sq1 = fmaf(lo, lo, fmaf(hi, hi, sq1)); }
            else { sx0 += lo + hi; sq0 = fmaf(lo, lo, fmaf(hi, hi, sq0)); }
          }
        }
        wg_wait<0>();
        #pragma unroll
        for (int kk = 0; kk < 4; kk++) asm volatile("" :: "r"(af[kk][0]), "r"(af[kk][1]), "r"(af[kk][2]), "r"(af[kk][3]));
        release_pair(B_AEMPTY + s);
      }
      reg_fence(acc); reg_fence(acr);
      if (tid == 0) PROF_T(2);
      const float mu0 = quad_sum(sx0) * (1.f / DM), mu1 = quad_sum(sx1) * (1.f / DM);
      const float rs0 = rsq(fmaxf(quad_sum(sq0) * (1.f / DM) - mu0 * mu0, 0.f) + 1e-5f), rs1 = rsq(fmaxf(quad_sum(sq1) * (1.f / DM) - mu1 * mu1, 0.f) + 1e-5f);
      const float mr0 = -mu0 * rs0, mr1 = -mu1 * rs1;
      mbar_wait(bar(B_STAT), 0, nspin);
      named_sync(1, 256);
      auto norm2 = [&](int sec, int t, uint32_t& lo, uint32_t& hi) {
        const float4 cs = lds_f4(sb + S_CS1 + (80 * sec + 8 * t + 2 * c4) * 8);
        const float* a = t < 8 ? &acc[4 * (8 * sec + t)] : &acr[4 * (2 * sec + t - 8)];
        lo = pack2(fmaf(a[0], rs0, cs.x * mr0), fmaf(a[1], rs0, cs.z * mr0));
        hi = pack2(fmaf(a[2], rs1, cs.x * mr1), fmaf(a[3], rs1, cs.z * mr1));
      };
      const uint32_t stA = sb + KV_OWN + (uint32_t)(rbw * 16 + ((lane >> 3) & 1) * 8 + (lane & 7)) * 16 + (uint32_t)(lane >> 4) * 2048;
      #pragma unroll
      for (int P = 1; P >= 0; P--) {
        const uint32_t base = stA + P * KV_HALF;
        uint32_t a0, a1, a2, a3;
        norm2(1, 5 * P, a0, a1); norm2(1, 5 * P + 1, a2, a3);
        stsm4(base, a0, a1, a2, a3);
        norm2(1, 5 * P + 2, a0, a1); norm2(1, 5 * P + 3, a2, a3);
        stsm4(base + 4096, a0, a1, a2, a3);
        norm2(1, 5 * P + 4, a0, a1); norm2(2, 5 * P, a2, a3);
        stsm4(base + 8192, a0, a1, a2, a3);
        norm2(2, 5 * P + 1, a0, a1); norm2(2, 5 * P + 2, a2, a3);
        const uint32_t one_e = c4 == 2 ? 0x3F80u : 0u, one_o = c4 == 0 ? 0x3F80u : 0u;
        stsm4(base + 12288, a0, a1, c4 < 2 ? a2 : one_e, c4 < 2 ? a3 : one_e);
        norm2(2, 5 * P + 3, a0, a1);
        stsm4(base + 16384, c4 < 2 ? one_o : a2, c4 < 2 ? one_o : a3, a0, a1);
        norm2(2, 5 * P + 4, a0, a1);
        stsm2(base + 20480, a0, a1);
        fence_async();
        __syncwarp();
        if (lane == 0) mbar_arrive(bar(B_KVW + 1 - P));
      }
      #pragma unroll
      for (int i = 0; i < 10; i++) norm2(0, i, qf[i][0], qf[i][1]);
      named_sync(1, 256);
      if (tid == 0) PROF_T(3);
    }
    {
      float A[32], B[32], O[12], svo[3][12], svm[3][2], m0 = 0.f, m1 = 0.f, c0 = 1.f, c1 = 1.f;
      uint32_t qa[8];
      const bool lowq = c4 < 2;
      const int w = rbw & 3, k0 = 2 * c4 <= g, k1 = 2 * c4 + 1 <= g;
      uint8_t* og = reinterpret_cast<uint8_t*>(&p.scr->o[(rbA * 8 + hq) * (OT_BYTES / 16)]) + (rbw * 16 + g) * 16 + c4 * 4;
      const uint32_t klo = desc_lo(sb, 2048), vlo = desc_lo(sb, 128);
      #pragma unroll
      for (int i = 0; i < 32; i++) A[i] = -INFINITY;
      #pragma unroll
      for (int i = 0; i < 12; i++) O[i] = 0.f;
      uint2 e1 = p.unit[wg][0];
      uint32_t v0 = vlo + (KV_OWN >> 4), y0 = 0;
      #pragma unroll 1
      for (int u = -1;; u++) {
        PROF_S(0);
        const uint32_t y1 = e1.y, st1 = y1 & 3, h1 = (y1 >> U_HSHIFT) & 3;
        const bool valid1 = (y1 & U_EXISTS) && (int)st1 <= rbA;
        const uint32_t base1 = (!valid1 || st1 == 0 ? KV_OWN : st1 == 1 ? KV_PREV : KV_FAR) >> 4;
        if (y1 & U_FIRST) {
          const uint32_t ml = lowq ? ~0u : 0u;
          if (h1 == 0)      { qa[0] = qf[0][0]; qa[1] = qf[0][1]; qa[2] = qf[1][0]; qa[3] = qf[1][1]; qa[4] = qf[2][0] & ml; qa[5] = qf[2][1] & ml; qa[6] = 0u; qa[7] = 0u; }
          else if (h1 == 1) { qa[0] = 0u; qa[1] = 0u; qa[2] = qf[2][0] & ~ml; qa[3] = qf[2][1] & ~ml; qa[4] = qf[3][0]; qa[5] = qf[3][1]; qa[6] = qf[4][0]; qa[7] = qf[4][1]; }
          else if (h1 == 2) { qa[0] = qf[5][0]; qa[1] = qf[5][1]; qa[2] = qf[6][0]; qa[3] = qf[6][1]; qa[4] = qf[7][0] & ml; qa[5] = qf[7][1] & ml; qa[6] = 0u; qa[7] = 0u; }
          else              { qa[0] = 0u; qa[1] = 0u; qa[2] = qf[7][0] & ~ml; qa[3] = qf[7][1] & ~ml; qa[4] = qf[8][0]; qa[5] = qf[8][1]; qa[6] = qf[9][0]; qa[7] = qf[9][1]; }
        }
        if (u == 3 && tid == 0) PROF_T(4);
        if (valid1 && (y1 & U_WAIT)) mbar_wait(bar(B_KVFULL + ((y1 >> U_WSHIFT) & 3)), 0, nspin);
        if (u == 3 && tid == 0) PROF_T(5);
        const uint32_t kb = klo + base1 + (e1.x & 0xffffu), v1 = vlo + base1 + (e1.x >> 16);
        wg_fence();
        wgmma_rs_n64_t0(B, qa[0], qa[1], qa[2], qa[3], desc<128, 0>(kb, 0), 0);
        wgmma_rs_n64_t0(B, qa[4], qa[5], qa[6], qa[7], desc<128, 0>(kb, 4096), 1);
        wg_commit();
        e1 = p.unit[wg][u + 2];
        #pragma unroll
        for (int i = 0; i < 16; i++) A[i] = ex2(A[i]);
        wg_wait<0>();
        reg_fence(B); reg_fence(O);
        PROF_S(1);
        if ((y0 & U_FIRST) || u == 20) {
          const uint32_t h0 = (y0 >> U_HSHIFT) & 3;
          if ((y0 & 3) == 0 && u != 20) {
            #pragma unroll
            for (int q = 0; q < 3; q++) if (h0 == q + 1) {
              #pragma unroll
              for (int i = 0; i < 12; i++) svo[q][i] = O[i];
            }
          } else {
            const int hf = u == 20 ? 0 : h0 + 1, odd = hf & 1;
            const int src = (lane & 28) | (odd ? 0 : 2);
            const float i0 = rcp(__shfl_sync(~0u, odd ? O[0] : O[8], src)), i1 = rcp(__shfl_sync(~0u, odd ? O[2] : O[10], src));
            uint8_t* o = og + (5 * (hf >> 1) + 2 * odd) * 2048;
            #pragma unroll
            for (int i = 0; i < 3; i++) {
              if (i == 1 || (i == 0 ? (!odd || !lowq) : (odd || lowq))) {
                *reinterpret_cast<uint32_t*>(o + i * 2048) = pack2(O[4 * i] * i0, O[4 * i + 1] * i0);
                *reinterpret_cast<uint32_t*>(o + i * 2048 + 128) = pack2(O[4 * i + 2] * i1, O[4 * i + 3] * i1);
              }
            }
            if (u == 20) break;
            #pragma unroll
            for (int q = 0; q < 3; q++) if (h0 == q) {
              #pragma unroll
              for (int i = 0; i < 12; i++) O[i] = svo[q][i];
            }
          }
        }
        #pragma unroll
        for (int i = 0; i < 3; i++) { O[4 * i] *= c0; O[4 * i + 1] *= c0; O[4 * i + 2] *= c1; O[4 * i + 3] *= c1; }
        if ((y1 & U_MASK) || !valid1) {
          const bool far = valid1 && st1 == 2;
          const int we = valid1 ? w : -8, thr0 = we + k0, thr1 = we + k1;
          #pragma unroll
          for (int b = 0; b < 4; b++) {
            float* e = &B[8 * b];
            const bool pa = (thr0 > b) != far, pb = (thr1 > b) != far, pc = (we >= b) != far, pd = (we > b) != far;
            e[0] = pa ? e[0] : -INFINITY; e[6] = pa ? e[6] : -INFINITY; e[1] = pb ? e[1] : -INFINITY; e[7] = pb ? e[7] : -INFINITY;
            e[2] = pc ? e[2] : -INFINITY; e[3] = pc ? e[3] : -INFINITY; e[4] = pd ? e[4] : -INFINITY; e[5] = pd ? e[5] : -INFINITY;
          }
        }
        float p0 = m0, p1 = m1;
        if (y1 & U_FIRST) {
          p0 = st1 == 0 ? -INFINITY : h1 == 0 ? svm[0][0] : h1 == 1 ? svm[1][0] : svm[2][0];
          p1 = st1 == 0 ? -INFINITY : h1 == 0 ? svm[0][1] : h1 == 1 ? svm[1][1] : svm[2][1];
        }
        uint32_t pf[4][4];
        #pragma unroll
        for (int i = 16; i < 32; i++) A[i] = ex2(A[i]);
        float mx0 = p0, mx1 = p1;
        #pragma unroll
        for (int b = 0; b < 4; b++) {
          const float* e = &B[8 * b];
          mx0 = fmaxf(mx0, fmaxf(fmaxf(e[0], e[1]), fmaxf(e[4], e[5])));
          mx1 = fmaxf(mx1, fmaxf(fmaxf(e[2], e[3]), fmaxf(e[6], e[7])));
          const float* a = &A[8 * b];
          pf[b][0] = pack2(a[0], a[1]); pf[b][1] = pack2(a[2], a[3]); pf[b][2] = pack2(a[4], a[5]); pf[b][3] = pack2(a[6], a[7]);
        }
        mx0 = quad_max(mx0); mx1 = quad_max(mx1);
        c0 = ex2((p0 - mx0) * SM_SCALE); c1 = ex2((p1 - mx1) * SM_SCALE);
        m0 = mx0; m1 = mx1;
        const float n0 = -mx0 * SM_SCALE, n1 = -mx1 * SM_SCALE;
        #pragma unroll
        for (int i = 0; i < 32; i++) A[i] = fmaf(B[i], SM_SCALE, (i & 2) ? n1 : n0);
        if (y1 & U_SAVEM) {
          #pragma unroll
          for (int q = 0; q < 3; q++) if (h1 == q) { svm[q][0] = mx0; svm[q][1] = mx1; }
        }
        PROF_S(2);
        reg_fence(O);
        wg_fence();
        #pragma unroll
        for (int b = 0; b < 4; b++) wgmma_rs_n24_t1(O, pf[b][0], pf[b][1], pf[b][2], pf[b][3], desc<2048, 0>(v0, b * 256), 1);
        wg_commit();
        PROF_S(3);
        v0 = v1; y0 = y1;
      }
      release_pair(B_ATTDONE);
      if (tid == 0) PROF_T(7);
      __syncwarp();
      if (lane == 0) red_release(&p.scr->flags[FL_O + rbA * 8 + hq], 1u);
      if (tid == 0) PROF_T(8);
    }
    const int r0 = warp * 16 + g;
    const uint32_t stsm_row = (uint32_t)(warp * 16 + ((lane >> 3) & 1) * 8 + (lane & 7)) * 16 + (uint32_t)(lane >> 4) * 2048;
    uint32_t hr[10][2];
    {
      const __nv_bfloat16* xp = p.x + (size_t)(rbC * 128 + r0) * DM + 80 * j + 2 * c4;
      #pragma unroll
      for (int t = 0; t < 10; t++) { hr[t][0] = ldg_u32(xp + 8 * t); hr[t][1] = ldg_u32(xp + 8 * DM + 8 * t); }
      float acc[40];
      const uint32_t alo = desc_lo(sb + wg * 1024, 2048), blo = desc_lo(sb, 4096);
      mbar_wait(bar(B_WOFULL), 0, nspin);
      #pragma unroll 1
      for (int t = 0; t < 8; t++) {
        const int s = t < 5 ? t : t - 5;
        mbar_wait(bar(B_CFULL + s), t >= 5, nspin);
        if (t == 6) mbar_wait(bar(B_WO4), 0, nspin);
        if (t == 0 && tid == 0) PROF_T(9);
        const uint32_t a = alo + s * (OT_BYTES >> 4);
        wg_fence();
        #pragma unroll
        for (int ks = 0; ks < 5; ks++) {
          const int k = 80 * t + 16 * ks;
          const uint32_t b = blo + (k >= 512 ? WO4_OFF >> 4 : (WO_OFF >> 4) + (k >> 7) * 1280) + (k & 127) * 2;
          wgmma_ss_n80_t1(acc, desc<128, 0>(a, ks * 4096), desc<256, 3>(b, 0), (t > 0 || ks > 0) ? 1 : 0);
        }
        wg_commit();
        wg_wait<1>();
        if (t >= 1 && t <= 3) release_pair(B_CEMPTY + t - 1);
      }
      wg_wait<0>();
      reg_fence(acc);
      release_pair(B_CDONE);
      if (tid == 0) PROF_T(10);
      named_sync(1, 256);
      float s0 = 0.f, q0 = 0.f, s1 = 0.f, q1 = 0.f;
      #pragma unroll
      for (int i = 0; i < 5; i++) {
        #pragma unroll
        for (int u = 0; u < 2; u++) {
          const int t = 2 * i + u;
          hr[t][0] = pack2(acc[4 * t] + bf_lo(hr[t][0]), acc[4 * t + 1] + bf_hi(hr[t][0]));
          hr[t][1] = pack2(acc[4 * t + 2] + bf_lo(hr[t][1]), acc[4 * t + 3] + bf_hi(hr[t][1]));
          const float a = bf_lo(hr[t][0]), b = bf_hi(hr[t][0]), c = bf_lo(hr[t][1]), d = bf_hi(hr[t][1]);
          s0 += a + b; q0 = fmaf(a, a, fmaf(b, b, q0)); s1 += c + d; q1 = fmaf(c, c, fmaf(d, d, q1));
        }
        stsm4(sb + i * 4096 + stsm_row, hr[2 * i][0], hr[2 * i][1], hr[2 * i + 1][0], hr[2 * i + 1][1]);
      }
      s0 = quad_sum(s0); q0 = quad_sum(q0); s1 = quad_sum(s1); q1 = quad_sum(q1);
      if (c4 == 0) { sts_f2(sb + 20480 + r0 * 8, s0, q0); sts_f2(sb + 20480 + (r0 + 8) * 8, s1, q1); }
      fence_async();
      __syncwarp();
      if (lane == 0) mbar_arrive(bar(B_HW));
      if (tid == 0) PROF_T(11);
    }
    {
      float acc[96];
      float hs0 = 0.f, hq0 = 0.f, hs1 = 0.f, hq1 = 0.f;
      const uint32_t alo = desc_lo(sb + wg * 1024, 2048), blo = desc_lo(sb + DB_OFF, 10240);
      #pragma unroll 1
      for (int t = 0; t < 8; t++) {
        const int s = t & 3;
        mbar_wait(bar(B_DBFULL + s), t >> 2, nspin);
        mbar_wait(bar(B_DAFULL + s), t >> 2, nspin);
        if (t == 0 && tid == 0) PROF_T(12);
        if (t == 2 && tid == 0) PROF_T(13);
        const uint32_t a = alo + s * (HT_BYTES >> 4), b = blo + s * (DB_SLOT >> 4);
        wg_fence();
        #pragma unroll
        for (int ks = 0; ks < 5; ks++)
          wgmma_ss_n192_t1(acc, desc<128, 0>(a, ks * 4096), desc<1024, 1>(b, ks * 2048), (t > 0 || ks > 0) ? 1 : 0);
        wg_commit();
        const float2 u0 = lds_f2(sb + s * HT_BYTES + 20480 + r0 * 8), u1 = lds_f2(sb + s * HT_BYTES + 20480 + (r0 + 8) * 8);
        hs0 += u0.x; hq0 += u0.y; hs1 += u1.x; hq1 += u1.y;
        wg_wait<1>();
        if (t > 0) { release_pair(B_DAEMPTY + ((t - 1) & 3)); if ((tid & 127) == 0) mbar_arrive(bar(B_DBEMPTY + ((t - 1) & 3))); }
      }
      wg_wait<0>();
      reg_fence(acc);
      if ((tid & 127) == 0) mbar_arrive(bar(B_DBEMPTY + 3));
      release_pair(B_DDONE);
      if (tid == 0) PROF_T(14);
      const float mu0 = hs0 * (1.f / DM), mu1 = hs1 * (1.f / DM);
      const float rs0 = rsq(fmaxf(hq0 * (1.f / DM) - mu0 * mu0, 0.f) + 1e-5f), rs1 = rsq(fmaxf(hq1 * (1.f / DM) - mu1 * mu1, 0.f) + 1e-5f);
      const float mr0 = -mu0 * rs0, mr1 = -mu1 * rs1;
      mbar_wait(bar(B_CS2), 0, nspin);
      named_sync(1, 256);
      #pragma unroll
      for (int i = 0; i < 12; i++) {
        uint32_t r[4];
        #pragma unroll
        for (int u = 0; u < 2; u++) {
          const int t = 2 * i + u;
          const float4 cb = lds_f4(sb + S_CS2 + (8 * t + 2 * c4) * 8);
          r[2 * u] = sq2(pack2_relu(fmaf(acc[4 * t], rs0, fmaf(cb.x, mr0, cb.y)), fmaf(acc[4 * t + 1], rs0, fmaf(cb.z, mr0, cb.w))));
          r[2 * u + 1] = sq2(pack2_relu(fmaf(acc[4 * t + 2], rs1, fmaf(cb.x, mr1, cb.y)), fmaf(acc[4 * t + 3], rs1, fmaf(cb.z, mr1, cb.w))));
        }
        stsm4(sb + rank * 49152 + i * 4096 + stsm_row, r[0], r[1], r[2], r[3]);
      }
      fence_async();
      __syncwarp();
      if (lane == 0) mbar_arrive(bar(B_FW));
      named_sync(2 + wg, 128);
      if (tid == 0) PROF_T(15);
    }
    {
      float acc1[96], acm[32], acr[32];
      const unsigned tag = lds_u32(sb + S_EPOCH);
      const uint32_t alo = desc_lo(sb + wg * 1024, 2048), blo = desc_lo(sb + EB_OFF, 8192), rlo = desc_lo(sb + EB_OFF + 8192, 2048);
      uint4* pbase = &p.scr->part[(size_t)((rbC * 2 + rank) * 16) * (8 * 5 * 32) + warp * 160 + lane];
      unsigned* fbase = &p.scr->flags[FL_P + ((rbC * 2 + rank) * 2 * 8 + warp) * 4];
      #pragma unroll 1
      for (int i = 0; i < 6; i++) {
        const int s = i % 5;
        mbar_wait(bar(B_EBFULL + s), i / 5, nspin);
        if (i >= 3) mbar_wait(bar(B_FFULL + i - 3), 0, nspin);
        const uint32_t a = alo + (i < 3 ? rank * 3072 + i * 1024 : (rank ^ 1) * 3072 + (i - 3) * 1024), b = blo + s * (EB_SLOT >> 4);
        wg_fence();
        #pragma unroll
        for (int ks = 0; ks < 4; ks++)
          wgmma_ss_n192_t1(acc1, desc<128, 0>(a, ks * 4096), desc<1024, 1>(b, ks * 2048), (i > 0 || ks > 0) ? 1 : 0);
        wg_commit();
        wg_wait<1>();
        if (i > 0 && (tid & 127) == 0) mbar_arrive(bar(B_EBEMPTY + (i - 1) % 5));
      }
      if (tid == 0) PROF_T(16);
      auto pass2_step = [&](int i) {
        const int s = i % 5;
        mbar_wait(bar(B_EBFULL + s), (i / 5) & 1, nspin);
        const int ks0 = i - 6;
        const uint32_t a = alo + (ks0 < 3 ? rank * 3072 + ks0 * 1024 : (rank ^ 1) * 3072 + (ks0 - 3) * 1024), so = s * (EB_SLOT >> 4);
        wg_fence();
        #pragma unroll
        for (int ks = 0; ks < 4; ks++) {
          const int sc = (i > 6 || ks > 0) ? 1 : 0;
          wgmma_ss_n64_t1(acm, desc<128, 0>(a, ks * 4096), desc<1024, 1>(blo + so, ks * 2048), sc);
          wgmma_ss_n64_t1(acr, desc<128, 0>(a, ks * 4096), desc<256, 3>(rlo + so, ks * 512), sc);
        }
        wg_commit();
        wg_wait<1>();
        if ((tid & 127) == 0) mbar_arrive(bar(B_EBEMPTY + (i - 1) % 5));
      };
      pass2_step(6);
      {
        reg_fence(acc1);
        #pragma unroll
        for (int q = 0; q < 3; q++) {
          uint4* d = pbase + (((jj + 1 + q) & 3) * 4 + jj) * 1280;
          #pragma unroll
          for (int u = 0; u < 4; u++) {
            const float* a1 = &acc1[32 * q + 8 * u];
            d[u * 32] = make_uint4(pack2(a1[0], a1[1]), pack2(a1[2], a1[3]), pack2(a1[4], a1[5]), pack2(a1[6], a1[7]));
          }
        }
        __syncwarp();
        if (lane == 0) st_release(fbase + jj, tag);
      }
      #pragma unroll 1
      for (int i = 7; i < 12; i++) pass2_step(i);
      wg_wait<0>();
      reg_fence(acm); reg_fence(acr);
      if (tid == 0) PROF_T(17);
      #pragma unroll
      for (int q = 0; q < 3; q++) {
        const float* a1 = &acr[8 * q];
        pbase[(((jj + 1 + q) & 3) * 4 + jj) * 1280 + 128] = make_uint4(pack2(a1[0], a1[1]), pack2(a1[2], a1[3]), pack2(a1[4], a1[5]), pack2(a1[6], a1[7]));
      }
      __syncwarp();
      if (lane == 0) st_release(fbase + 32 + jj, tag);
      const __nv_bfloat16* b2p = p.b2 + 80 * j + 2 * c4;
      float k[40];
      #pragma unroll
      for (int t = 0; t < 10; t++) {
        const uint32_t bb = ldg_u32(b2p + 8 * t);
        const float* a1 = t < 8 ? &acm[4 * t] : &acr[24 + 4 * (t - 8)];
        k[4 * t] = a1[0] + bf_lo(bb) + bf_lo(hr[t][0]); k[4 * t + 1] = a1[1] + bf_hi(bb) + bf_hi(hr[t][0]);
        k[4 * t + 2] = a1[2] + bf_lo(bb) + bf_lo(hr[t][1]); k[4 * t + 3] = a1[3] + bf_hi(bb) + bf_hi(hr[t][1]);
      }
      __nv_bfloat16* op = p.out + (size_t)(rbC * 128 + r0) * DM + 80 * j + 2 * c4;
      #pragma unroll
      for (int pass = 0; pass < 2; pass++) {
        while (++nspin < SPIN_LIMIT) {
          const unsigned v = ld_relaxed(fbase + pass * 32 + (lane & 3));
          if (__all_sync(~0u, (lane & 3) == jj || (int)(v - tag) >= 0)) break;
        }
        #pragma unroll
        for (int d = 1; d < 4; d++) {
          const uint4* src = pbase + (jj * 4 + ((jj + d) & 3)) * 1280;
          #pragma unroll
          for (int u = (pass ? 4 : 0); u < (pass ? 5 : 4); u++) {
            const uint4 v = ldg_cg_u4(src + u * 32);
            float* kk = &k[8 * u];
            kk[0] += bf_lo(v.x); kk[1] += bf_hi(v.x); kk[2] += bf_lo(v.y); kk[3] += bf_hi(v.y);
            kk[4] += bf_lo(v.z); kk[5] += bf_hi(v.z); kk[6] += bf_lo(v.w); kk[7] += bf_hi(v.w);
          }
        }
        #pragma unroll
        for (int t = (pass ? 8 : 0); t < (pass ? 10 : 8); t++) {
          *reinterpret_cast<uint32_t*>(op + 8 * t) = pack2(k[4 * t], k[4 * t + 1]);
          *reinterpret_cast<uint32_t*>(op + 8 * DM + 8 * t) = pack2(k[4 * t + 2], k[4 * t + 3]);
        }
      }
      if (tid == 0) PROF_T(18);
    }
  }
  __syncwarp();
  cluster_arrive();
  cluster_wait();
}

typedef CUresult (*EncodeTiledFn)(CUtensorMap*, CUtensorMapDataType, cuuint32_t, void*, const cuuint64_t*, const cuuint64_t*, const cuuint32_t*,
                                  const cuuint32_t*, CUtensorMapInterleave, CUtensorMapSwizzle, CUtensorMapL2promotion, CUtensorMapFloatOOBfill);

static bool encode_map(EncodeTiledFn fn, CUtensorMap* m, const void* ptr, int rank, const cuuint64_t* dims, const cuuint64_t* strides, const cuuint32_t* box,
                       CUtensorMapSwizzle sw) {
  const cuuint32_t es[3] = {1, 1, 1};
  return fn(m, CU_TENSOR_MAP_DATA_TYPE_BFLOAT16, rank, const_cast<void*>(ptr), dims, strides, box, es, CU_TENSOR_MAP_INTERLEAVE_NONE, sw,
            CU_TENSOR_MAP_L2_PROMOTION_L2_256B, CU_TENSOR_MAP_FLOAT_OOB_FILL_NONE) == CUDA_SUCCESS;
}

static void attention_schedule(Params& p) {
  for (int wg = 0; wg < 2; wg++) {
    int n = 0;
    auto add = [&](int h, int st, bool d, bool first, bool last_own) {
      const uint32_t P = h >> 1, odd = h & 1, half = d ? wg : 1 - wg;
      const uint32_t ko = (P * KV_HALF + odd * 2048 + half * 1024) >> 4, vo = (P * KV_HALF + 10240 + odd * 6144 + half * 1024) >> 4;
      uint32_t y = st | (h << U_HSHIFT) | U_EXISTS;
      if (d && st != 1) y |= U_MASK;
      if (first) y |= U_FIRST;
      if (last_own && h < 3) y |= U_SAVEM;
      if (st > 0 && d && odd) y |= U_WAIT | ((uint32_t)((st - 1) + 2 * (1 - P)) << U_WSHIFT);
      p.unit[wg][n++] = make_uint2(ko | (vo << 16), y);
    };
    for (int h = 0; h < 4; h++) { add(h, 0, true, true, wg == 0); if (wg == 1) add(h, 0, false, false, true); }
    for (int h = 3; h >= 0; h--) {
      add(h, 1, true, h < 3, false); add(h, 1, false, false, false); add(h, 2, true, false, false);
      if (wg == 0) add(h, 2, false, false, false);
    }
    for (; n < 24; n++) p.unit[wg][n] = make_uint2(p.unit[wg][0].x, 0);
  }
}

}

extern "C" void kernel_launch(void* const* d_in, const int* in_sizes, int n_in, void* d_out, int out_size) {
  using namespace blk;
  (void)in_sizes; (void)n_in; (void)out_size;
  static EncodeTiledFn encode = nullptr;
  static void* scratch = nullptr;
  if (!encode) {
    cudaDriverEntryPointQueryResult st;
    void* fn = nullptr;
    if (cudaGetDriverEntryPoint("cuTensorMapEncodeTiled", &fn, cudaEnableDefault, &st) != cudaSuccess || !fn) return;
    encode = reinterpret_cast<EncodeTiledFn>(fn);
    cudaFuncSetAttribute(fused_block_kernel, cudaFuncAttributeMaxDynamicSharedMemorySize, SMEM_BYTES);
    cudaGetSymbolAddress(&scratch, g_scr);
  }
  Params p;
  p.x = static_cast<const __nv_bfloat16*>(d_in[0]); p.wqkv = static_cast<const __nv_bfloat16*>(d_in[1]); p.wo = static_cast<const __nv_bfloat16*>(d_in[2]);
  p.w1 = static_cast<const __nv_bfloat16*>(d_in[4]); p.b1 = static_cast<const __nv_bfloat16*>(d_in[5]);
  p.w2 = static_cast<const __nv_bfloat16*>(d_in[6]); p.b2 = static_cast<const __nv_bfloat16*>(d_in[7]); p.out = static_cast<__nv_bfloat16*>(d_out);
  p.scr = static_cast<Scratch*>(scratch);
  attention_schedule(p);
  CUtensorMap mX, mWq, mWr, mWo, mW1, mW2, mW2r;
  bool ok = true;
  { cuuint64_t d[2] = {DM, SEQ}, s[1] = {DM * 2}; cuuint32_t b[2] = {64, 128}; ok &= encode_map(encode, &mX, p.x, 2, d, s, b, CU_TENSOR_MAP_SWIZZLE_128B); }
  { cuuint64_t d[3] = {DM, DM, 3}, s[2] = {3 * DM * 2, DM * 2}; cuuint32_t b[3] = {64, 32, 3}; ok &= encode_map(encode, &mWq, p.wqkv, 3, d, s, b, CU_TENSOR_MAP_SWIZZLE_128B); }
  { cuuint64_t d[3] = {DM, DM, 3}, s[2] = {3 * DM * 2, DM * 2}; cuuint32_t b[3] = {16, 32, 3}; ok &= encode_map(encode, &mWr, p.wqkv, 3, d, s, b, CU_TENSOR_MAP_SWIZZLE_32B); }
  { cuuint64_t d[3] = {16, DM, DM / 16}, s[2] = {DM * 2, 32}; cuuint32_t b[3] = {16, 128, 5}; ok &= encode_map(encode, &mWo, p.wo, 3, d, s, b, CU_TENSOR_MAP_SWIZZLE_32B); }
  { cuuint64_t d[2] = {FF, DM}, s[1] = {FF * 2}; cuuint32_t b[2] = {64, 80}; ok &= encode_map(encode, &mW1, p.w1, 2, d, s, b, CU_TENSOR_MAP_SWIZZLE_128B); }
  { cuuint64_t d[2] = {DM, FF}, s[1] = {DM * 2}; cuuint32_t b[2] = {64, 64}; ok &= encode_map(encode, &mW2, p.w2, 2, d, s, b, CU_TENSOR_MAP_SWIZZLE_128B); }
  { cuuint64_t d[2] = {DM, FF}, s[1] = {DM * 2}; cuuint32_t b[2] = {16, 64}; ok &= encode_map(encode, &mW2r, p.w2, 2, d, s, b, CU_TENSOR_MAP_SWIZZLE_32B); }
  if (!ok) return;
  cudaLaunchConfig_t cfg = {};
  cfg.gridDim = dim3(NCTA); cfg.blockDim = dim3(384); cfg.dynamicSmemBytes = SMEM_BYTES; cfg.stream = cudaStreamPerThread;
  cudaLaunchAttribute at[1];
  at[0].id = cudaLaunchAttributeClusterDimension; at[0].val.clusterDim.x = 2; at[0].val.clusterDim.y = 1; at[0].val.clusterDim.z = 1;
  cfg.attrs = at; cfg.numAttrs = 1;
  cudaLaunchKernelEx(&cfg, fused_block_kernel, mX, mWq, mWr, mWo, mW1, mW2, mW2r, p);
}
```

```cpp
#include <cuda_runtime.h>
#include <cuda.h>
#include <cuda_bf16.h>
#include <stdint.h>

namespace blk {

constexpr int SEQ = 2048, DM = 640, FF = 1536;
constexpr int NCTA = 128;

constexpr uint32_t A_STAGE = 47104;
constexpr uint32_t CS_STG0 = 188416, CS_STG1 = 217088;
constexpr uint32_t KV_HALF = 22528, KV_BLK = 45056;
constexpr uint32_t KV_FAR = 0, KV_PREV = 45056, KV_OWN = 90112;
constexpr uint32_t WO_OFF = 135168, WO4_OFF = 102400;
constexpr uint32_t OT_BYTES = 20480;
constexpr uint32_t HT_BYTES = 21504;
constexpr uint32_t DB_OFF = 98304, DB_SLOT = 30720;
constexpr uint32_t EB_OFF = 98304, EB_SLOT = 24576;
constexpr uint32_t AUX = 225280;
constexpr uint32_t BARS = AUX;
constexpr uint32_t S_CS1 = AUX + 512;
constexpr uint32_t S_CS2 = AUX + 2560;
constexpr uint32_t S_EPOCH = AUX + 4096;
constexpr uint32_t S_KC = AUX + 4096 + 128;
constexpr uint32_t S_PROF = S_KC + 1024;
constexpr uint32_t SMEM_BYTES = S_PROF;

enum Bar : int {
  B_AFULL = 0  , B_AEMPTY = 4  ,
  B_STAT = 8, B_KVFULL = 9  , B_KVST = 13, B_AUXDONE = 14, B_WOFULL = 15, B_CFULL = 16  , B_WO4 = 21, B_DAFULL = 22  , B_DBFULL = 26  ,
  B_FFULL = 30  , B_EBFULL = 33  , B_CS2 = 38, B_EPOCH = 39, B_AUX2 = 40,
  B_DBEMPTY = 41  , B_EBEMPTY = 45  , B_KVW = 50  , B_HW = 52, B_FW = 53, B_DAEMPTY = 54  , B_ATTDONE = 58, B_CEMPTY = 59  ,
  B_CDONE = 62, B_DDONE = 63, B_COUNT = 64
};
__device__ __forceinline__ uint32_t bar_count(int i) { return i < B_DBEMPTY ? 1 : i < B_KVW ? 2 : i < B_DAEMPTY ? 8 : i == B_DAEMPTY ? 6 : 4; }

constexpr int FL_EPOCH = 0, FL_KV = 128, FL_O = 384, FL_H = 512, FL_P = 640;
struct Scratch {
  uint4 kv[128 * (KV_BLK / 16)];
  uint4 o[128 * (OT_BYTES / 16)];
  uint4 h[128 * (HT_BYTES / 16)];
  uint4 part[16 * 2 * 4 * 4 * 8 * 5 * 32];
  unsigned long long cs[3 * DM + FF];
  unsigned flags[640 + 16 * 2 * 2 * 8 * 4];
};
__device__ __align__(1024) Scratch g_scr;
#define PROF_T(i) do {} while (0)
#define PROF_G(k) do {} while (0)
#define PROF_S(k) do {} while (0)

__device__ __forceinline__ uint32_t smem_u32(const void* p) { return (uint32_t)__cvta_generic_to_shared(p); }
__device__ __forceinline__ void mbar_init(uint32_t bar, uint32_t cnt) { asm volatile("mbarrier.init.shared::cta.b64 [%0], %1;" :: "r"(bar), "r"(cnt)); }
__device__ __forceinline__ void mbar_expect_tx(uint32_t bar, uint32_t bytes) { asm volatile("mbarrier.arrive.expect_tx.shared::cta.b64 _, [%0], %1;" :: "r"(bar), "r"(bytes) : "memory"); }
__device__ __forceinline__ void mbar_arrive(uint32_t bar) { asm volatile("mbarrier.arrive.shared::cta.b64 _, [%0];" :: "r"(bar) : "memory"); }
__device__ __forceinline__ uint32_t mapa(uint32_t addr, uint32_t cta) { uint32_t r; asm volatile("mapa.shared::cluster.u32 %0, %1, %2;" : "=r"(r) : "r"(addr), "r"(cta)); return r; }
__device__ __forceinline__ void mbar_arrive_cluster(uint32_t bar, uint32_t cta) {
  asm volatile("{\n.reg .b32 ra;\nmapa.shared::cluster.u32 ra, %0, %1;\nmbarrier.arrive.shared::cluster.b64 _, [ra];\n}" :: "r"(bar), "r"(cta) : "memory");
}
constexpr unsigned SPIN_LIMIT = 1u << 22;
__device__ __forceinline__ void mbar_wait(uint32_t bar, uint32_t parity, unsigned& n) {
  asm volatile("{\n.reg .pred p, q;\nWAIT_%=:\nmbarrier.try_wait.parity.shared::cta.b64 p, [%1], %2;\n@!p add.u32 %0, %0, 1;\n"
               "setp.lt.and.u32 q, %0, %3, !p;\n@q bra WAIT_%=;\n}" : "+&r"(n) : "r"(bar), "r"(parity), "n"(SPIN_LIMIT) : "memory");
}
__device__ __forceinline__ uint32_t mbar_probe(uint32_t bar, uint32_t need) {
  uint32_t ok;
  asm volatile("{\n.reg .pred p;\nsetp.eq.u32 p, %2, 0;\n@!p mbarrier.test_wait.parity.shared::cta.b64 p, [%1], 0;\nselp.u32 %0, 1, 0, p;\n}" : "=r"(ok) : "r"(bar), "r"(need) : "memory");
  return ok;
}
__device__ __forceinline__ void mbar_wait_probed(uint32_t bar, uint32_t ok, unsigned& n) {
  asm volatile("{\n.reg .pred p, q;\nsetp.ne.u32 p, %2, 0;\nWAIT_%=:\n@!p mbarrier.try_wait.parity.shared::cta.b64 p, [%1], 0;\n@!p add.u32 %0, %0, 1;\n"
               "setp.lt.and.u32 q, %0, %3, !p;\n@q bra WAIT_%=;\n}" : "+&r"(n) : "r"(bar), "r"(ok), "n"(SPIN_LIMIT) : "memory");
}
__device__ __forceinline__ unsigned ld_relaxed(const unsigned* p) { unsigned v; asm volatile("ld.relaxed.gpu.global.u32 %0, [%1];" : "=r"(v) : "l"(p) : "memory"); return v; }
__device__ __forceinline__ unsigned ld_acquire(const unsigned* p) { unsigned v; asm volatile("ld.acquire.gpu.global.u32 %0, [%1];" : "=r"(v) : "l"(p) : "memory"); return v; }
__device__ __forceinline__ unsigned long long ld_relaxed64(const unsigned long long* p) { unsigned long long v; asm volatile("ld.relaxed.gpu.global.u64 %0, [%1];" : "=l"(v) : "l"(p) : "memory"); return v; }
__device__ __forceinline__ void st_relaxed(unsigned* p, unsigned v) { asm volatile("st.relaxed.gpu.global.u32 [%0], %1;" :: "l"(p), "r"(v) : "memory"); }
__device__ __forceinline__ void st_relaxed64(unsigned long long* p, unsigned lo, unsigned hi) {
  asm volatile("{\n.reg .b64 v;\nmov.b64 v, {%1, %2};\nst.relaxed.gpu.global.u64 [%0], v;\n}" :: "l"(p), "r"(lo), "r"(hi) : "memory");
}
__device__ __forceinline__ void st_release(unsigned* p, unsigned v) { asm volatile("st.release.gpu.global.u32 [%0], %1;" :: "l"(p), "r"(v) : "memory"); }
__device__ __forceinline__ void red_release(unsigned* p, unsigned v) { asm volatile("red.release.gpu.global.add.u32 [%0], %1;" :: "l"(p), "r"(v) : "memory"); }
__device__ __forceinline__ void fence_acq() { asm volatile("fence.acq_rel.gpu;" ::: "memory"); }
__device__ __forceinline__ void fence_async() { asm volatile("fence.proxy.async.shared::cta;" ::: "memory"); }
__device__ __forceinline__ void fence_async_global() { asm volatile("fence.proxy.async.global;" ::: "memory"); }
__device__ __forceinline__ bool elect_one() {
  uint32_t r;
  asm volatile("{\n.reg .pred P;\nelect.sync _|P, 0xffffffff;\nselp.u32 %0, 1, 0, P;\n}" : "=r"(r));
  return r != 0;
}
__device__ __forceinline__ void wait_flag(const unsigned* p, unsigned target, unsigned& n) {
  while ((int)(ld_acquire(p) - target) < 0 && ++n < SPIN_LIMIT) {}
}
__device__ __forceinline__ void tma_2d(uint32_t dst, const CUtensorMap* map, int c0, int c1, uint32_t bar) {
  asm volatile("cp.async.bulk.tensor.2d.shared::cluster.global.mbarrier::complete_tx::bytes [%0], [%1, {%3, %4}], [%2];"
    :: "r"(dst), "l"(map), "r"(bar), "r"(c0), "r"(c1) : "memory");
}
__device__ __forceinline__ void tma_3d(uint32_t dst, const CUtensorMap* map, int c0, int c1, int c2, uint32_t bar) {
  asm volatile("cp.async.bulk.tensor.3d.shared::cluster.global.mbarrier::complete_tx::bytes [%0], [%1, {%3, %4, %5}], [%2];"
    :: "r"(dst), "l"(map), "r"(bar), "r"(c0), "r"(c1), "r"(c2) : "memory");
}
__device__ __forceinline__ void tma_3d_mc(uint32_t dst, const CUtensorMap* map, int c0, int c1, int c2, uint32_t bar) {
  asm volatile("cp.async.bulk.tensor.3d.shared::cluster.global.mbarrier::complete_tx::bytes.multicast::cluster [%0], [%1, {%3, %4, %5}], [%2], %6;"
    :: "r"(dst), "l"(map), "r"(bar), "r"(c0), "r"(c1), "r"(c2), "h"((uint16_t)3) : "memory");
}
__device__ __forceinline__ void bulk_ld(uint32_t dst, const void* src, uint32_t bytes, uint32_t bar) {
  asm volatile("cp.async.bulk.shared::cluster.global.mbarrier::complete_tx::bytes [%0], [%1], %2, [%3];" :: "r"(dst), "l"(src), "r"(bytes), "r"(bar) : "memory");
}
__device__ __forceinline__ void bulk_ld_mc(uint32_t dst, const void* src, uint32_t bytes, uint32_t bar) {
  asm volatile("cp.async.bulk.shared::cluster.global.mbarrier::complete_tx::bytes.multicast::cluster [%0], [%1], %2, [%3], %4;"
    :: "r"(dst), "l"(src), "r"(bytes), "r"(bar), "h"((uint16_t)3) : "memory");
}
__device__ __forceinline__ void bulk_st(void* dst, uint32_t src, uint32_t bytes) {
  asm volatile("cp.async.bulk.global.shared::cta.bulk_group [%0], [%1], %2;" :: "l"(dst), "r"(src), "r"(bytes) : "memory");
}
__device__ __forceinline__ void bulk_dsmem(uint32_t rdst, uint32_t src, uint32_t bytes, uint32_t rbar) {
  asm volatile("cp.async.bulk.shared::cluster.shared::cta.mbarrier::complete_tx::bytes [%0], [%1], %2, [%3];" :: "r"(rdst), "r"(src), "r"(bytes), "r"(rbar) : "memory");
}
__device__ __forceinline__ void bulk_commit() { asm volatile("cp.async.bulk.commit_group;" ::: "memory"); }
__device__ __forceinline__ void bulk_wait0() { asm volatile("cp.async.bulk.wait_group 0;" ::: "memory"); }
__device__ __forceinline__ void bulk_wait1() { asm volatile("cp.async.bulk.wait_group 1;" ::: "memory"); }
__device__ __forceinline__ void prefetch_l2(const void* p, uint32_t bytes) { asm volatile("cp.async.bulk.prefetch.L2.global [%0], %1;" :: "l"(p), "r"(bytes) : "memory"); }
__device__ __forceinline__ void prefetch_map(const CUtensorMap* m) { asm volatile("prefetch.tensormap [%0];" :: "l"(m) : "memory"); }
__device__ __forceinline__ void cp_async16(uint32_t dst, const void* src) { asm volatile("cp.async.cg.shared.global [%0], [%1], 16;" :: "r"(dst), "l"(src) : "memory"); }
__device__ __forceinline__ void cp_async_wait_all() { asm volatile("cp.async.wait_all;" ::: "memory"); }
__device__ __forceinline__ void cluster_arrive() { asm volatile("barrier.cluster.arrive.release.aligned;" ::: "memory"); }
__device__ __forceinline__ void cluster_wait() { asm volatile("barrier.cluster.wait.acquire.aligned;" ::: "memory"); }
__device__ __forceinline__ void named_sync(int id, int n) { asm volatile("bar.sync %0, %1;" :: "r"(id), "r"(n) : "memory"); }
__device__ __forceinline__ void wg_fence() { asm volatile("wgmma.fence.sync.aligned;" ::: "memory"); }
__device__ __forceinline__ void wg_commit() { asm volatile("wgmma.commit_group.sync.aligned;" ::: "memory"); }
template <int N> __device__ __forceinline__ void wg_wait() { asm volatile("wgmma.wait_group.sync.aligned %0;" :: "n"(N) : "memory"); }
template <int N> __device__ __forceinline__ void reg_fence(float (&d)[N]) {
  #pragma unroll
  for (int i = 0; i < N; i++) asm volatile("" : "+f"(d[i]) :: "memory");
}
__device__ __forceinline__ uint32_t desc_lo(uint32_t addr, uint32_t lbo) { return ((addr & 0x3FFFF) >> 4) | ((lbo >> 4) << 16); }
template <uint32_t SBO, uint32_t SWZ> __device__ __forceinline__ uint64_t desc(uint32_t lo, uint32_t byte_off) {
  return ((uint64_t)((SBO >> 4) | (SWZ << 30)) << 32) | (uint64_t)(lo + (byte_off >> 4));
}
__device__ __forceinline__ uint32_t pack2(float lo, float hi) { uint32_t r; asm("cvt.rn.bf16x2.f32 %0, %1, %2;" : "=r"(r) : "f"(hi), "f"(lo)); return r; }
__device__ __forceinline__ uint32_t pack2_relu(float lo, float hi) { uint32_t r; asm("cvt.rn.relu.bf16x2.f32 %0, %1, %2;" : "=r"(r) : "f"(hi), "f"(lo)); return r; }
__device__ __forceinline__ uint32_t sq2(uint32_t v) { uint32_t r; asm("mul.rn.bf16x2 %0, %1, %1;" : "=r"(r) : "r"(v)); return r; }
__device__ __forceinline__ float bf_lo(uint32_t v) { return __uint_as_float(v << 16); }
__device__ __forceinline__ float bf_hi(uint32_t v) { return __uint_as_float(v & 0xffff0000u); }
__device__ __forceinline__ float ex2(float x) { float r; asm("ex2.approx.ftz.f32 %0, %1;" : "=f"(r) : "f"(x)); return r; }
__device__ __forceinline__ float rcp(float x) { float r; asm("rcp.approx.ftz.f32 %0, %1;" : "=f"(r) : "f"(x)); return r; }
__device__ __forceinline__ float rsq(float x) { float r; asm("rsqrt.approx.ftz.f32 %0, %1;" : "=f"(r) : "f"(x)); return r; }
__device__ __forceinline__ void stsm4(uint32_t addr, uint32_t a, uint32_t b, uint32_t c, uint32_t d) {
  asm volatile("stmatrix.sync.aligned.m8n8.x4.shared.b16 [%0], {%1, %2, %3, %4};" :: "r"(addr), "r"(a), "r"(b), "r"(c), "r"(d) : "memory");
}
__device__ __forceinline__ void stsm2(uint32_t addr, uint32_t a, uint32_t b) {
  asm volatile("stmatrix.sync.aligned.m8n8.x2.shared.b16 [%0], {%1, %2};" :: "r"(addr), "r"(a), "r"(b) : "memory");
}
__device__ __forceinline__ void ldsm4(uint32_t addr, uint32_t (&r)[4]) {
  asm volatile("ldmatrix.sync.aligned.m8n8.x4.shared.b16 {%0, %1, %2, %3}, [%4];" : "=r"(r[0]), "=r"(r[1]), "=r"(r[2]), "=r"(r[3]) : "r"(addr) : "memory");
}
__device__ __forceinline__ float2 lds_f2(uint32_t a) { float2 v; asm volatile("ld.shared.v2.f32 {%0, %1}, [%2];" : "=f"(v.x), "=f"(v.y) : "r"(a)); return v; }
__device__ __forceinline__ float4 lds_f4(uint32_t a) { float4 v; asm volatile("ld.shared.v4.f32 {%0, %1, %2, %3}, [%4];" : "=f"(v.x), "=f"(v.y), "=f"(v.z), "=f"(v.w) : "r"(a)); return v; }
__device__ __forceinline__ uint4 lds_u4(uint32_t a) { uint4 v; asm volatile("ld.shared.v4.u32 {%0, %1, %2, %3}, [%4];" : "=r"(v.x), "=r"(v.y), "=r"(v.z), "=r"(v.w) : "r"(a)); return v; }
__device__ __forceinline__ void sts_f2(uint32_t a, float x, float y) { asm volatile("st.shared.v2.f32 [%0], {%1, %2};" :: "r"(a), "f"(x), "f"(y) : "memory"); }
__device__ __forceinline__ void sts_u4(uint32_t a, uint32_t x, uint32_t y, uint32_t z, uint32_t w) { asm volatile("st.shared.v4.u32 [%0], {%1, %2, %3, %4};" :: "r"(a), "r"(x), "r"(y), "r"(z), "r"(w) : "memory"); }
__device__ __forceinline__ void sts_u32(uint32_t a, uint32_t x) { asm volatile("st.shared.u32 [%0], %1;" :: "r"(a), "r"(x) : "memory"); }
__device__ __forceinline__ uint32_t lds_u32(uint32_t a) { uint32_t v; asm volatile("ld.shared.u32 %0, [%1];" : "=r"(v) : "r"(a) : "memory"); return v; }
__device__ __forceinline__ uint32_t ldg_u32(const void* p) { uint32_t v; asm volatile("ld.global.nc.u32 %0, [%1];" : "=r"(v) : "l"(p)); return v; }
__device__ __forceinline__ uint4 ldg_cg_u4(const void* p) { uint4 v; asm volatile("ld.global.cg.v4.u32 {%0, %1, %2, %3}, [%4];" : "=r"(v.x), "=r"(v.y), "=r"(v.z), "=r"(v.w) : "l"(p) : "memory"); return v; }
__device__ __forceinline__ float quad_max(float v) { v = fmaxf(v, __shfl_xor_sync(~0u, v, 1)); return fmaxf(v, __shfl_xor_sync(~0u, v, 2)); }
__device__ __forceinline__ float quad_sum(float v) { v += __shfl_xor_sync(~0u, v, 1); return v + __shfl_xor_sync(~0u, v, 2); }

__device__ __forceinline__ void wgmma_rs_n192_t1(float (&d)[96], uint32_t a0, uint32_t a1, uint32_t a2, uint32_t a3, uint64_t db, int scale_d) {
  asm volatile("{\n.reg .pred p;\nsetp.ne.b32 p, %101, 0;\nwgmma.mma_async.sync.aligned.m64n192k16.f32.bf16.bf16 {%0, %1, %2, %3, %4, %5, %6, %7, %8, %9, %10, %11, %12, %13, %14, %15, %16, %17, %18, %19, %20, %21, %22, %23, %24, %25, %26, %27, %28, %29, %30, %31, %32, %33, %34, %35, %36, %37, %38, %39, %40, %41, %42, %43, %44, %45, %46, %47, %48, %49, %50, %51, %52, %53, %54, %55, %56, %57, %58, %59, %60, %61, %62, %63, %64, %65, %66, %67, %68, %69, %70, %71, %72, %73, %74, %75, %76, %77, %78, %79, %80, %81, %82, %83, %84, %85, %86, %87, %88, %89, %90, %91, %92, %93, %94, %95}, {%96, %97, %98, %99}, %100, p, 1, 1, 1;\n}"
    : "+f"(d[0]), "+f"(d[1]), "+f"(d[2]), "+f"(d[3]), "+f"(d[4]), "+f"(d[5]), "+f"(d[6]), "+f"(d[7]), "+f"(d[8]), "+f"(d[9]), "+f"(d[10]), "+f"(d[11]), "+f"(d[12]), "+f"(d[13]), "+f"(d[14]), "+f"(d[15]), "+f"(d[16]), "+f"(d[17]), "+f"(d[18]), "+f"(d[19]), "+f"(d[20]), "+f"(d[21]), "+f"(d[22]), "+f"(d[23]), "+f"(d[24]), "+f"(d[25]), "+f"(d[26]), "+f"(d[27]), "+f"(d[28]), "+f"(d[29]), "+f"(d[30]), "+f"(d[31]), "+f"(d[32]), "+f"(d[33]), "+f"(d[34]), "+f"(d[35]), "+f"(d[36]), "+f"(d[37]), "+f"(d[38]), "+f"(d[39]), "+f"(d[40]), "+f"(d[41]), "+f"(d[42]), "+f"(d[43]), "+f"(d[44]), "+f"(d[45]), "+f"(d[46]), "+f"(d[47]), "+f"(d[48]), "+f"(d[49]), "+f"(d[50]), "+f"(d[51]), "+f"(d[52]), "+f"(d[53]), "+f"(d[54]), "+f"(d[55]), "+f"(d[56]), "+f"(d[57]), "+f"(d[58]), "+f"(d[59]), "+f"(d[60]), "+f"(d[61]), "+f"(d[62]), "+f"(d[63]), "+f"(d[64]), "+f"(d[65]), "+f"(d[66]), "+f"(d[67]), "+f"(d[68]), "+f"(d[69]), "+f"(d[70]), "+f"(d[71]), "+f"(d[72]), "+f"(d[73]), "+f"(d[74]), "+f"(d[75]), "+f"(d[76]), "+f"(d[77]), "+f"(d[78]), "+f"(d[79]), "+f"(d[80]), "+f"(d[81]), "+f"(d[82]), "+f"(d[83]), "+f"(d[84]), "+f"(d[85]), "+f"(d[86]), "+f"(d[87]), "+f"(d[88]), "+f"(d[89]), "+f"(d[90]), "+f"(d[91]), "+f"(d[92]), "+f"(d[93]), "+f"(d[94]), "+f"(d[95])
    : "r"(a0), "r"(a1), "r"(a2), "r"(a3), "l"(db), "r"(scale_d));
}

__device__ __forceinline__ void wgmma_rs_n48_t1(float (&d)[24], uint32_t a0, uint32_t a1, uint32_t a2, uint32_t a3, uint64_t db, int scale_d) {
  asm volatile("{\n.reg .pred p;\nsetp.ne.b32 p, %29, 0;\nwgmma.mma_async.sync.aligned.m64n48k16.f32.bf16.bf16 {%0, %1, %2, %3, %4, %5, %6, %7, %8, %9, %10, %11, %12, %13, %14, %15, %16, %17, %18, %19, %20, %21, %22, %23}, {%24, %25, %26, %27}, %28, p, 1, 1, 1;\n}"
    : "+f"(d[0]), "+f"(d[1]), "+f"(d[2]), "+f"(d[3]), "+f"(d[4]), "+f"(d[5]), "+f"(d[6]), "+f"(d[7]), "+f"(d[8]), "+f"(d[9]), "+f"(d[10]), "+f"(d[11]), "+f"(d[12]), "+f"(d[13]), "+f"(d[14]), "+f"(d[15]), "+f"(d[16]), "+f"(d[17]), "+f"(d[18]), "+f"(d[19]), "+f"(d[20]), "+f"(d[21]), "+f"(d[22]), "+f"(d[23])
    : "r"(a0), "r"(a1), "r"(a2), "r"(a3), "l"(db), "r"(scale_d));
}

__device__ __forceinline__ void wgmma_rs_n64_t0(float (&d)[32], uint32_t a0, uint32_t a1, uint32_t a2, uint32_t a3, uint64_t db, int scale_d) {
  asm volatile("{\n.reg .pred p;\nsetp.ne.b32 p, %37, 0;\nwgmma.mma_async.sync.aligned.m64n64k16.f32.bf16.bf16 {%0, %1, %2, %3, %4, %5, %6, %7, %8, %9, %10, %11, %12, %13, %14, %15, %16, %17, %18, %19, %20, %21, %22, %23, %24, %25, %26, %27, %28, %29, %30, %31}, {%32, %33, %34, %35}, %36, p, 1, 1, 0;\n}"
    : "+f"(d[0]), "+f"(d[1]), "+f"(d[2]), "+f"(d[3]), "+f"(d[4]), "+f"(d[5]), "+f"(d[6]), "+f"(d[7]), "+f"(d[8]), "+f"(d[9]), "+f"(d[10]), "+f"(d[11]), "+f"(d[12]), "+f"(d[13]), "+f"(d[14]), "+f"(d[15]), "+f"(d[16]), "+f"(d[17]), "+f"(d[18]), "+f"(d[19]), "+f"(d[20]), "+f"(d[21]), "+f"(d[22]), "+f"(d[23]), "+f"(d[24]), "+f"(d[25]), "+f"(d[26]), "+f"(d[27]), "+f"(d[28]), "+f"(d[29]), "+f"(d[30]), "+f"(d[31])
    : "r"(a0), "r"(a1), "r"(a2), "r"(a3), "l"(db), "r"(scale_d));
}

__device__ __forceinline__ void wgmma_rs_n24_t1(float (&d)[12], uint32_t a0, uint32_t a1, uint32_t a2, uint32_t a3, uint64_t db, int scale_d) {
  asm volatile("{\n.reg .pred p;\nsetp.ne.b32 p, %17, 0;\nwgmma.mma_async.sync.aligned.m64n24k16.f32.bf16.bf16 {%0, %1, %2, %3, %4, %5, %6, %7, %8, %9, %10, %11}, {%12, %13, %14, %15}, %16, p, 1, 1, 1;\n}"
    : "+f"(d[0]), "+f"(d[1]), "+f"(d[2]), "+f"(d[3]), "+f"(d[4]), "+f"(d[5]), "+f"(d[6]), "+f"(d[7]), "+f"(d[8]), "+f"(d[9]), "+f"(d[10]), "+f"(d[11])
    : "r"(a0), "r"(a1), "r"(a2), "r"(a3), "l"(db), "r"(scale_d));
}

__device__ __forceinline__ void wgmma_ss_n80_t1(float (&d)[40], uint64_t da, uint64_t db, int scale_d) {
  asm volatile("{\n.reg .pred p;\nsetp.ne.b32 p, %42, 0;\nwgmma.mma_async.sync.aligned.m64n80k16.f32.bf16.bf16 {%0, %1, %2, %3, %4, %5, %6, %7, %8, %9, %10, %11, %12, %13, %14, %15, %16, %17, %18, %19, %20, %21, %22, %23, %24, %25, %26, %27, %28, %29, %30, %31, %32, %33, %34, %35, %36, %37, %38, %39}, %40, %41, p, 1, 1, 0, 1;\n}"
    : "+f"(d[0]), "+f"(d[1]), "+f"(d[2]), "+f"(d[3]), "+f"(d[4]), "+f"(d[5]), "+f"(d[6]), "+f"(d[7]), "+f"(d[8]), "+f"(d[9]), "+f"(d[10]), "+f"(d[11]), "+f"(d[12]), "+f"(d[13]), "+f"(d[14]), "+f"(d[15]), "+f"(d[16]), "+f"(d[17]), "+f"(d[18]), "+f"(d[19]), "+f"(d[20]), "+f"(d[21]), "+f"(d[22]), "+f"(d[23]), "+f"(d[24]), "+f"(d[25]), "+f"(d[26]), "+f"(d[27]), "+f"(d[28]), "+f"(d[29]), "+f"(d[30]), "+f"(d[31]), "+f"(d[32]), "+f"(d[33]), "+f"(d[34]), "+f"(d[35]), "+f"(d[36]), "+f"(d[37]), "+f"(d[38]), "+f"(d[39])
    : "l"(da), "l"(db), "r"(scale_d));
}

__device__ __forceinline__ void wgmma_ss_n192_t1(float (&d)[96], uint64_t da, uint64_t db, int scale_d) {
  asm volatile("{\n.reg .pred p;\nsetp.ne.b32 p, %98, 0;\nwgmma.mma_async.sync.aligned.m64n192k16.f32.bf16.bf16 {%0, %1, %2, %3, %4, %5, %6, %7, %8, %9, %10, %11, %12, %13, %14, %15, %16, %17, %18, %19, %20, %21, %22, %23, %24, %25, %26, %27, %28, %29, %30, %31, %32, %33, %34, %35, %36, %37, %38, %39, %40, %41, %42, %43, %44, %45, %46, %47, %48, %49, %50, %51, %52, %53, %54, %55, %56, %57, %58, %59, %60, %61, %62, %63, %64, %65, %66, %67, %68, %69, %70, %71, %72, %73, %74, %75, %76, %77, %78, %79, %80, %81, %82, %83, %84, %85, %86, %87, %88, %89, %90, %91, %92, %93, %94, %95}, %96, %97, p, 1, 1, 0, 1;\n}"
    : "+f"(d[0]), "+f"(d[1]), "+f"(d[2]), "+f"(d[3]), "+f"(d[4]), "+f"(d[5]), "+f"(d[6]), "+f"(d[7]), "+f"(d[8]), "+f"(d[9]), "+f"(d[10]), "+f"(d[11]), "+f"(d[12]), "+f"(d[13]), "+f"(d[14]), "+f"(d[15]), "+f"(d[16]), "+f"(d[17]), "+f"(d[18]), "+f"(d[19]), "+f"(d[20]), "+f"(d[21]), "+f"(d[22]), "+f"(d[23]), "+f"(d[24]), "+f"(d[25]), "+f"(d[26]), "+f"(d[27]), "+f"(d[28]), "+f"(d[29]), "+f"(d[30]), "+f"(d[31]), "+f"(d[32]), "+f"(d[33]), "+f"(d[34]), "+f"(d[35]), "+f"(d[36]), "+f"(d[37]), "+f"(d[38]), "+f"(d[39]), "+f"(d[40]), "+f"(d[41]), "+f"(d[42]), "+f"(d[43]), "+f"(d[44]), "+f"(d[45]), "+f"(d[46]), "+f"(d[47]), "+f"(d[48]), "+f"(d[49]), "+f"(d[50]), "+f"(d[51]), "+f"(d[52]), "+f"(d[53]), "+f"(d[54]), "+f"(d[55]), "+f"(d[56]), "+f"(d[57]), "+f"(d[58]), "+f"(d[59]), "+f"(d[60]), "+f"(d[61]), "+f"(d[62]), "+f"(d[63]), "+f"(d[64]), "+f"(d[65]), "+f"(d[66]), "+f"(d[67]), "+f"(d[68]), "+f"(d[69]), "+f"(d[70]), "+f"(d[71]), "+f"(d[72]), "+f"(d[73]), "+f"(d[74]), "+f"(d[75]), "+f"(d[76]), "+f"(d[77]), "+f"(d[78]), "+f"(d[79]), "+f"(d[80]), "+f"(d[81]), "+f"(d[82]), "+f"(d[83]), "+f"(d[84]), "+f"(d[85]), "+f"(d[86]), "+f"(d[87]), "+f"(d[88]), "+f"(d[89]), "+f"(d[90]), "+f"(d[91]), "+f"(d[92]), "+f"(d[93]), "+f"(d[94]), "+f"(d[95])
    : "l"(da), "l"(db), "r"(scale_d));
}

__device__ __forceinline__ void wgmma_ss_n64_t1(float (&d)[32], uint64_t da, uint64_t db, int scale_d) {
  asm volatile("{\n.reg .pred p;\nsetp.ne.b32 p, %34, 0;\nwgmma.mma_async.sync.aligned.m64n64k16.f32.bf16.bf16 {%0, %1, %2, %3, %4, %5, %6, %7, %8, %9, %10, %11, %12, %13, %14, %15, %16, %17, %18, %19, %20, %21, %22, %23, %24, %25, %26, %27, %28, %29, %30, %31}, %32, %33, p, 1, 1, 0, 1;\n}"
    : "+f"(d[0]), "+f"(d[1]), "+f"(d[2]), "+f"(d[3]), "+f"(d[4]), "+f"(d[5]), "+f"(d[6]), "+f"(d[7]), "+f"(d[8]), "+f"(d[9]), "+f"(d[10]), "+f"(d[11]), "+f"(d[12]), "+f"(d[13]), "+f"(d[14]), "+f"(d[15]), "+f"(d[16]), "+f"(d[17]), "+f"(d[18]), "+f"(d[19]), "+f"(d[20]), "+f"(d[21]), "+f"(d[22]), "+f"(d[23]), "+f"(d[24]), "+f"(d[25]), "+f"(d[26]), "+f"(d[27]), "+f"(d[28]), "+f"(d[29]), "+f"(d[30]), "+f"(d[31])
    : "l"(da), "l"(db), "r"(scale_d));
}

struct Params {
  const __nv_bfloat16* x; const __nv_bfloat16* wqkv; const __nv_bfloat16* wo; const __nv_bfloat16* w1;
  const __nv_bfloat16* b1; const __nv_bfloat16* w2; const __nv_bfloat16* b2; __nv_bfloat16* out; Scratch* scr;
  uint32_t sched[3][2][12];
};
enum : uint32_t { S_OWN = 1u << 19, S_FAR = 2u << 19, S_MASK = 3u << 19  , S_WAIT = 1u << 21  ,
                  S_OSW = 1u << 24  , S_END = 1u << 27, S_CUR = 1u << 29   };
constexpr float SM_SCALE = 0.22360679774997896f * 1.4426950408889634f;

__global__ void __launch_bounds__(384, 1)
fused_block_kernel(const __grid_constant__ CUtensorMap mX, const __grid_constant__ CUtensorMap mWq, const __grid_constant__ CUtensorMap mWr,
                   const __grid_constant__ CUtensorMap mWo, const __grid_constant__ CUtensorMap mW1, const __grid_constant__ CUtensorMap mW2,
                   const __grid_constant__ CUtensorMap mW2r, const __grid_constant__ Params p) {
  extern __shared__ __align__(1024) uint8_t smem_raw[];
  const uint32_t sb = smem_u32(smem_raw);
  const int tid = threadIdx.x, lane = tid & 31;
  const int warp = __shfl_sync(~0u, tid >> 5, 0);
  const int cta = blockIdx.x, rank = cta & 1, pair = cta >> 1;
  const int hq = pair & 7, rbA = (pair >> 3) * 2 + rank;
  const int rbC = pair >> 2, jj = pair & 3, j = jj * 2 + rank;
  const uint32_t bars = sb + BARS;
  auto bar = [&](int i) { return bars + i * 8; };
  unsigned nspin = 0;

  if (warp == 8) {
    if (elect_one()) {
      PROF_T(0);
      prefetch_map(&mX); prefetch_map(&mWq); prefetch_map(&mWr);
      #pragma unroll
      for (int i = 0; i < 4; i++) { mbar_init(bar(B_AFULL + i), 1); mbar_init(bar(B_AEMPTY + i), 4); }
      asm volatile("fence.mbarrier_init.release.cluster;" ::: "memory");
      fence_async();
      #pragma unroll 1
      for (int it = 0; it < 4; it++) { mbar_expect_tx(bar(B_AFULL + it), A_STAGE); tma_2d(sb + it * A_STAGE, &mX, it * 64, rbA * 128, bar(B_AFULL + it)); }
    }
    __syncwarp();
  }
  asm volatile("barrier.cluster.arrive.relaxed.aligned;" ::: "memory");
  if (warp != 8 && elect_one()) {
    #pragma unroll 1
    for (int i = 8 + (warp < 8 ? warp : warp - 1); i < B_COUNT; i += 11) mbar_init(bar(i), bar_count(i));
    asm volatile("fence.mbarrier_init.release.cluster;" ::: "memory");
  }
  __syncwarp();
  cluster_wait();
  auto w_loads = [&](int it) {
    const uint32_t full = bar(B_AFULL + (it & 3)), dst = sb + (it & 3) * A_STAGE + 16384 + rank * 15360;
    tma_3d_mc(dst, &mWq, 80 * hq, it * 64 + 32 * rank, 0, full);
    tma_3d_mc(dst + 12288, &mWr, 80 * hq + 64, it * 64 + 32 * rank, 0, full);
  };
  if (warp == 8 && elect_one()) {
    #pragma unroll 1
    for (int it = 0; it < 4; it++) w_loads(it);
    PROF_T(27);
  }
  __syncthreads();

  if (warp >= 8) {
    asm volatile("setmaxnreg.dec.sync.aligned.u32 56;");
    if (warp == 11) {
      const unsigned tag = ld_relaxed(&p.scr->flags[FL_EPOCH + cta]) + 1u;
      #pragma unroll 1
      for (int job = 0; job < 2; job++) {
        if (job) mbar_wait(bar(B_KVW), 0, nspin);
        if (cta < (job ? 96 : 120)) {
          const int ld = job ? FF : 3 * DM, batch = job ? 16 : 40;
          const __nv_bfloat16* src = (job ? p.w1 : p.wqkv) + (size_t)(lane >> 1) * ld + cta * 16 + (lane & 1) * 8;
          const uint32_t sl = sb + (job ? CS_STG1 : CS_STG0) + lane * 16;
          float acc[8];
          #pragma unroll
          for (int i = 0; i < 8; i++) acc[i] = 0.f;
          #pragma unroll 1
          for (int r0 = 0; r0 < 40; r0 += batch) {
            const int n = 40 - r0 < batch ? 40 - r0 : batch;
            #pragma unroll 1
            for (int i = 0; i < n; i++) { cp_async16(sl + i * 512, src); src += 16 * ld; }
            cp_async_wait_all();
            #pragma unroll 1
            for (int i = 0; i < n; i++) {
              const uint4 v = lds_u4(sl + i * 512);
              acc[0] += bf_lo(v.x); acc[1] += bf_hi(v.x); acc[2] += bf_lo(v.y); acc[3] += bf_hi(v.y);
              acc[4] += bf_lo(v.z); acc[5] += bf_hi(v.z); acc[6] += bf_lo(v.w); acc[7] += bf_hi(v.w);
            }
          }
          #pragma unroll
          for (int o = 0; o < 3; o++) {
            const bool up = (lane >> (o + 1)) & 1;
            #pragma unroll
            for (int i = 0; i < (4 >> o); i++) {
              const float keep = up ? acc[2 * i + 1] : acc[2 * i], give = up ? acc[2 * i] : acc[2 * i + 1];
              acc[i] = keep + __shfl_xor_sync(~0u, give, 2 << o);
            }
          }
          const float v = acc[0] + __shfl_xor_sync(~0u, acc[0], 16);
          if (lane < 16) st_relaxed64(&p.scr->cs[(job ? 3 * DM : 0) + cta * 16 + (lane & 1) * 8 + (lane >> 1)], __float_as_uint(v), tag);
        }
        __syncwarp();
        if (elect_one()) {
          mbar_arrive(bar(job ? B_AUX2 : B_AUXDONE));
          if (job == 0) {
            st_relaxed(&p.scr->flags[FL_EPOCH + cta], tag);
            sts_u32(sb + S_EPOCH, tag);
            mbar_arrive(bar(B_EPOCH));
            PROF_T(26);
            prefetch_l2(reinterpret_cast<const uint8_t*>(p.wo) + cta * 6400, 6400);
            prefetch_l2(reinterpret_cast<const uint8_t*>(p.w1) + cta * 15360, 15360);
            prefetch_l2(reinterpret_cast<const uint8_t*>(p.w2) + cta * 15360, 15360);
          }
        }
        __syncwarp();
        const int n = job ? 96 : 120;
        const uint32_t dst = sb + (job ? S_CS2 : S_CS1);
        const uint4* csrc = reinterpret_cast<const uint4*>(job ? &p.scr->cs[3 * DM + 192 * j] : &p.scr->cs[80 * hq]);
        bool ok;
        do {
          #pragma unroll 1
          for (int c = lane; c < n; c += 32) cp_async16(dst + c * 16, csrc + c + (job ? 0 : (c >= 40 ? 280 : 0) + (c >= 80 ? 280 : 0)));
          cp_async_wait_all();
          ok = true;
          #pragma unroll 1
          for (int c = lane; c < n; c += 32) { const uint4 v = lds_u4(dst + c * 16); ok = ok && v.y == tag && v.w == tag; }
          ok = __all_sync(~0u, ok);
        } while (!ok && ++nspin < SPIN_LIMIT);
        if (job) {
          #pragma unroll 1
          for (int c = lane; c < 96; c += 32) {
            const uint32_t bb = ldg_u32(p.b1 + 192 * j + 2 * c);
            sts_u32(dst + c * 16 + 4, bb << 16); sts_u32(dst + c * 16 + 12, bb & 0xffff0000u);
          }
        }
        __syncwarp();
        if (lane == 0) { mbar_arrive(bar(job ? B_CS2 : B_STAT)); if (job == 0) PROF_T(23); }
      }
    } else if (warp == 10) {
      mbar_wait(bar(B_EPOCH), 0, nspin);
      const unsigned tag = lds_u32(sb + S_EPOCH);
      if (elect_one()) {
        uint4* kvg = &p.scr->kv[(rbA * 8 + hq) * (KV_BLK / 16)];
        unsigned* kvf = &p.scr->flags[FL_KV + (rbA * 8 + hq) * 2];
        mbar_wait(bar(B_KVW), 0, nspin);
        bulk_st(kvg + KV_HALF / 16, sb + KV_OWN + KV_HALF, KV_HALF);
        bulk_commit();
        mbar_wait(bar(B_KVW + 1), 0, nspin);
        bulk_st(kvg, sb + KV_OWN, KV_HALF);
        bulk_commit();
        bulk_wait1(); fence_async_global(); st_release(kvf, tag);
        PROF_T(28);
        bulk_wait0(); fence_async_global(); st_release(kvf + 1, tag);
        mbar_arrive(bar(B_KVST));
        PROF_T(24);
        mbar_wait(bar(B_HW), 0, nspin);
        mbar_arrive(bar(B_DAFULL + 0));
        bulk_st(&p.scr->h[(rbC * 8 + j) * (HT_BYTES / 16)], sb, HT_BYTES);
        bulk_commit();
        mbar_wait(bar(B_CDONE), 0, nspin);
        bulk_dsmem(mapa(sb + HT_BYTES, rank ^ 1), sb, HT_BYTES, mapa(bar(B_DAFULL + 1), rank ^ 1));
        bulk_wait0();
        fence_async_global();
        st_release(&p.scr->flags[FL_H + rbC * 8 + j], tag);
        mbar_arrive_cluster(bar(B_DAEMPTY + 0), 0); mbar_arrive_cluster(bar(B_DAEMPTY + 0), 1);
        PROF_T(25);
        mbar_wait(bar(B_FW), 0, nspin); mbar_wait(bar(B_DDONE), 0, nspin);
        #pragma unroll 1
        for (int i = 0; i < 3; i++) {
          const uint32_t off = rank * 49152 + i * 16384;
          bulk_dsmem(mapa(sb + off, rank ^ 1), sb + off, 16384, mapa(bar(B_FFULL + i), rank ^ 1));
        }
      }
    } else if (warp == 9) {
      mbar_wait(bar(B_EPOCH), 0, nspin);
      const unsigned tag = lds_u32(sb + S_EPOCH);
      if (elect_one()) {
        mbar_wait(bar(B_KVW), 0, nspin);
        #pragma unroll 1
        for (int c = 0; c < 4; c++) {
          const int d = 1 + (c & 1), blk = (rbA - d) * 8 + hq;
          const uint32_t off = c < 2 ? KV_HALF : 0;
          if (rbA >= d) {
            wait_flag(&p.scr->flags[FL_KV + blk * 2 + (c >> 1)], tag, nspin);
            fence_async_global();
            mbar_expect_tx(bar(B_KVFULL + c), KV_HALF);
            bulk_ld(sb + (d == 1 ? KV_PREV : KV_FAR) + off, reinterpret_cast<const uint8_t*>(p.scr->kv) + blk * KV_BLK + off, KV_HALF, bar(B_KVFULL + c));
          }
        }
        mbar_wait(bar(B_KVST), 0, nspin);
        mbar_wait(bar(B_AUXDONE), 0, nspin);
        mbar_expect_tx(bar(B_WOFULL), 81920);
        #pragma unroll 1
        for (int kb = 0; kb < 4; kb++) tma_3d(sb + WO_OFF + kb * 20480, &mWo, 0, kb * 128, 5 * j, bar(B_WOFULL));
        PROF_T(20);
      }
      #pragma unroll 1
      for (int job = 0; job < 2; job++) {
        const uint32_t bytes = job ? HT_BYTES : OT_BYTES, half = bytes >> 1;
        if (elect_one()) {
          if (job == 0) {
            mbar_wait(bar(B_ATTDONE), 0, nspin);
            mbar_expect_tx(bar(B_WO4), 20480);
            tma_3d(sb + WO4_OFF, &mWo, 0, 512, 5 * j, bar(B_WO4));
          }
          else {
            mbar_expect_tx(bar(B_DAFULL + 1), HT_BYTES);
            #pragma unroll 1
            for (int i = 0; i < 3; i++) mbar_expect_tx(bar(B_FFULL + i), 16384);
            mbar_wait(bar(B_CDONE), 0, nspin);
          }
        }
        __syncwarp();
        const unsigned* fl = &p.scr->flags[(job ? FL_H : FL_O) + rbC * 8 + (lane & 7)];
        const uint8_t* src = (job ? reinterpret_cast<const uint8_t*>(p.scr->h) : reinterpret_cast<const uint8_t*>(p.scr->o)) + rbC * 8 * bytes + rank * half;
        const unsigned target = job ? tag : tag * 8u;
        int next = job * 2;
        while (next < 8 && ++nspin < SPIN_LIMIT) {
          const unsigned ready = __ballot_sync(~0u, (int)(ld_acquire(fl) - target) >= 0);
          bool first = true;
          while (next < 8) {
            const int kt = job ? ((jj + (next >> 1)) & 3) * 2 + (next & 1) : next;
            if (!((ready >> kt) & 1)) break;
            if (elect_one()) {
              if (first) fence_async_global();
              const int s = job ? next & 3 : next < 5 ? next : next - 5;
              if (next >= (job ? 4 : 5)) mbar_wait(bar((job ? B_DAEMPTY : B_CEMPTY) + s), 0, nspin);
              if (job && next == 4) mbar_wait(bar(B_DAEMPTY + 1), 0, nspin);
              const uint32_t full = bar((job ? B_DAFULL : B_CFULL) + s);
              mbar_expect_tx(full, bytes);
              bulk_ld_mc(sb + s * bytes + rank * half, src + kt * bytes, half, full);
            }
            first = false;
            next++;
          }
        }
        if (lane == 0) PROF_T(21 + job);
      }
    } else {
      if (elect_one()) {
        #pragma unroll 1
        for (int it = 4; it < 10; it++) {
          const int s = it & 3;
          mbar_wait(bar(B_AEMPTY + s), ((it >> 2) - 1) & 1, nspin);
          mbar_expect_tx(bar(B_AFULL + s), A_STAGE);
          tma_2d(sb + s * A_STAGE, &mX, it * 64, rbA * 128, bar(B_AFULL + s));
          w_loads(it);
        }
        prefetch_map(&mWo); prefetch_map(&mW1); prefetch_map(&mW2); prefetch_map(&mW2r);
        mbar_wait(bar(B_AUX2), 0, nspin);
        mbar_wait(bar(B_CDONE), 0, nspin);
        #pragma unroll 1
        for (int t = 0; t < 8; t++) {
          const int s = t & 3;
          if (t >= 4) mbar_wait(bar(B_DBEMPTY + s), 0, nspin);
          const int kt = t < 2 ? (j ^ t) : (((jj + (t >> 1)) & 3) * 2 + (t & 1));
          const uint32_t full = bar(B_DBFULL + s), dst = sb + DB_OFF + s * DB_SLOT;
          mbar_expect_tx(full, 30720);
          #pragma unroll 1
          for (int c = 0; c < 3; c++) tma_2d(dst + c * 10240, &mW1, 192 * j + 64 * c, 80 * kt, full);
        }
        #pragma unroll 1
        for (int i = 0; i < 12; i++) {
          const int s = i < 5 ? i : i < 10 ? i - 5 : i - 10, ks = i < 6 ? i : i - 6;
          mbar_wait(bar(i < 4 ? B_DBEMPTY + i : B_EBEMPTY + s), i < 4 ? 1 : i >= 10 ? 1 : i >= 5 ? 0 : 1, nspin);
          const int krow = 384 * jj + (ks < 3 ? 192 * rank + 64 * ks : 192 * (rank ^ 1) + 64 * (ks - 3));
          const uint32_t full = bar(B_EBFULL + s), dst = sb + EB_OFF + s * EB_SLOT;
          mbar_expect_tx(full, i < 6 ? 24576 : 16384);
          #pragma unroll 1
          for (int c = 0; c < (i < 6 ? 3 : 1); c++) tma_2d(dst + c * 8192, &mW2, 160 * ((jj + (i < 6 ? 1 + c : 0)) & 3) + 80 * rank, krow, full);
          if (i >= 6) {
            #pragma unroll 1
            for (int c = 0; c < 4; c++) tma_2d(dst + 8192 + c * 2048, &mW2r, 160 * ((jj + 1 + c) & 3) + 80 * rank + 64, krow, full);
          }
        }
      }
    }
  } else {
    asm volatile("setmaxnreg.inc.sync.aligned.u32 224;");
    const int wg = warp >> 2, g = lane >> 2, c4 = lane & 3;
    auto release_pair = [&](int b) { if ((tid & 127) < 2) mbar_arrive_cluster(bar(b), tid & 1); };
    if (tid < 64) { sts_u4(sb + S_KC + tid * 16, 0x3F803F80u, 0x3F80u, tid < 16 ? 0x3F80u : tid < 32 ? 0x3F800000u : 0u, tid >= 48 ? 0x3F800000u : tid >= 32 ? 0x3F80u : 0u); fence_async(); }
    const int rbw = warp < 4 ? warp : 11 - warp;
    uint32_t qf[10][2];
    {
      float acc[96], acr[24];
      float sx0 = 0.f, sq0 = 0.f, sx1 = 0.f, sq1 = 0.f;
      const uint32_t arow = rbw * 16 + (lane & 7) + ((lane >> 3) & 1) * 8;
      const uint32_t aoff = sb + arow * 128 + (((lane >> 4) ^ (arow & 7)) << 4);
      const uint32_t lo192 = desc_lo(sb + 16384, 4096), lo48 = desc_lo(sb + 16384 + 12288, 1024);
      #pragma unroll 1
      for (int it = 0; it < 10; it++) {
        const int s = it & 3;
        mbar_wait(bar(B_AFULL + s), (it >> 2) & 1, nspin);
        if (it == 0 && tid == 0) PROF_T(1);
        const uint32_t so = s * A_STAGE;
        uint32_t af[4][4];
        #pragma unroll
        for (int kk = 0; kk < 4; kk++) ldsm4((aoff ^ (kk * 32)) + so, af[kk]);
        wg_fence();
        #pragma unroll
        for (int kk = 0; kk < 4; kk++) {
          const int sc = (it > 0 || kk > 0) ? 1 : 0;
          wgmma_rs_n192_t1(acc, af[kk][0], af[kk][1], af[kk][2], af[kk][3], desc<1024, 1>(lo192 + (so >> 4), (kk >> 1) * 15360 + (kk & 1) * 2048), sc);
          wgmma_rs_n48_t1(acr, af[kk][0], af[kk][1], af[kk][2], af[kk][3], desc<256, 3>(lo48 + (so >> 4), (kk >> 1) * 15360 + (kk & 1) * 512), sc);
        }
        wg_commit();
        #pragma unroll
        for (int kk = 0; kk < 4; kk++) {
          #pragma unroll
          for (int u = 0; u < 4; u++) {
            const float lo = bf_lo(af[kk][u]), hi = bf_hi(af[kk][u]);
            if (u & 1) { sx1 += lo + hi; sq1 = fmaf(lo, lo, fmaf(hi, hi, sq1)); }
            else { sx0 += lo + hi; sq0 = fmaf(lo, lo, fmaf(hi, hi, sq0)); }
          }
        }
        wg_wait<0>();
        #pragma unroll
        for (int kk = 0; kk < 4; kk++) asm volatile("" :: "r"(af[kk][0]), "r"(af[kk][1]), "r"(af[kk][2]), "r"(af[kk][3]));
        release_pair(B_AEMPTY + s);
      }
      reg_fence(acc); reg_fence(acr);
      if (tid == 0) PROF_T(2);
      const float mu0 = quad_sum(sx0) * (1.f / DM), mu1 = quad_sum(sx1) * (1.f / DM);
      const float rs0 = rsq(fmaxf(quad_sum(sq0) * (1.f / DM) - mu0 * mu0, 0.f) + 1e-5f), rs1 = rsq(fmaxf(quad_sum(sq1) * (1.f / DM) - mu1 * mu1, 0.f) + 1e-5f);
      const float mr0 = -mu0 * rs0, mr1 = -mu1 * rs1;
      mbar_wait(bar(B_STAT), 0, nspin);
      named_sync(1, 256);
      auto norm2 = [&](int sec, int t, uint32_t& lo, uint32_t& hi) {
        const float4 cs = lds_f4(sb + S_CS1 + (80 * sec + 8 * t + 2 * c4) * 8);
        const float* a = t < 8 ? &acc[4 * (8 * sec + t)] : &acr[4 * (2 * sec + t - 8)];
        const float r0 = sec ? rs0 : rs0 * SM_SCALE, r1 = sec ? rs1 : rs1 * SM_SCALE, n0 = sec ? mr0 : mr0 * SM_SCALE, n1 = sec ? mr1 : mr1 * SM_SCALE;
        lo = pack2(fmaf(a[0], r0, cs.x * n0), fmaf(a[1], r0, cs.z * n0));
        hi = pack2(fmaf(a[2], r1, cs.x * n1), fmaf(a[3], r1, cs.z * n1));
      };
      const uint32_t stA = sb + KV_OWN + (uint32_t)(rbw * 16 + ((lane >> 3) & 1) * 8 + (lane & 7)) * 16 + (uint32_t)(lane >> 4) * 2048;
      #pragma unroll
      for (int P = 1; P >= 0; P--) {
        const uint32_t base = stA + P * KV_HALF;
        uint32_t a0, a1, a2, a3;
        norm2(1, 5 * P, a0, a1); norm2(1, 5 * P + 1, a2, a3);
        stsm4(base, a0, a1, a2, a3);
        norm2(1, 5 * P + 2, a0, a1); norm2(1, 5 * P + 3, a2, a3);
        stsm4(base + 4096, a0, a1, a2, a3);
        norm2(1, 5 * P + 4, a0, a1); norm2(2, 5 * P, a2, a3);
        stsm4(base + 8192, a0, a1, a2, a3);
        norm2(2, 5 * P + 1, a0, a1); norm2(2, 5 * P + 2, a2, a3);
        const uint32_t one_e = c4 == 2 ? 0x3F80u : 0u, one_o = c4 == 0 ? 0x3F80u : 0u;
        stsm4(base + 12288, a0, a1, c4 < 2 ? a2 : one_e, c4 < 2 ? a3 : one_e);
        norm2(2, 5 * P + 3, a0, a1);
        stsm4(base + 16384, c4 < 2 ? one_o : a2, c4 < 2 ? one_o : a3, a0, a1);
        norm2(2, 5 * P + 4, a0, a1);
        stsm2(base + 20480, a0, a1);
        fence_async();
        __syncwarp();
        if (lane == 0) mbar_arrive(bar(B_KVW + 1 - P));
      }
      #pragma unroll
      for (int i = 0; i < 10; i++) norm2(0, i, qf[i][0], qf[i][1]);
      named_sync(1, 256);
      if (tid == 0) PROF_T(3);
    }
    {
      float A[32], B[32], Oe[12], Oo[12], Xe[12], Xo[12];
      uint32_t qe[6], qo[6], ye[6], yo[6];
      uint32_t sh[4] = {0u, 0u, 0u, 0u}, xh[4] = {0u, 0u, 0u, 0u};
      uint32_t z0, z1, z2, z3;
      const bool lowq = c4 < 2;
      {
        const uint32_t ml = lowq ? ~0u : 0u;
        qe[0] = qf[0][0]; qe[1] = qf[0][1]; qe[2] = qf[1][0]; qe[3] = qf[1][1]; qe[4] = qf[2][0] & ml; qe[5] = qf[2][1] & ml;
        qo[0] = qf[2][0] & ~ml; qo[1] = qf[2][1] & ~ml; qo[2] = qf[3][0]; qo[3] = qf[3][1]; qo[4] = qf[4][0]; qo[5] = qf[4][1];
        ye[0] = qf[5][0]; ye[1] = qf[5][1]; ye[2] = qf[6][0]; ye[3] = qf[6][1]; ye[4] = qf[7][0] & ml; ye[5] = qf[7][1] & ml;
        yo[0] = qf[7][0] & ~ml; yo[1] = qf[7][1] & ~ml; yo[2] = qf[8][0]; yo[3] = qf[8][1]; yo[4] = qf[9][0]; yo[5] = qf[9][1];
      }
      const int w = rbw & 3;
      const int b0 = 2 * c4 - 4;
      const uint32_t zown = lowq ? 0u : (b0 > w ? 0xF180u : 0u) | (b0 + 1 > w ? 0xF1800000u : 0u);
      const uint32_t zfar = lowq ? 0u : (b0 < w ? 0xF180u : 0u) | (b0 + 1 < w ? 0xF1800000u : 0u);
      const uint32_t zvoid = lowq ? 0u : 0xF180F180u;
      auto zmask = [&](uint32_t e) {
        const uint32_t lo = 0u - ((e >> 19) & 1u), hi = 0u - ((e >> 20) & 1u);
        return (zown & lo & ~hi) | (zfar & hi & ~lo) | (zvoid & lo & hi);
      };
      const uint32_t mk = (2 * c4 <= g ? 0xffffu : 0u) | (2 * c4 + 1 <= g ? 0xffff0000u : 0u);
      uint8_t* og = reinterpret_cast<uint8_t*>(&p.scr->o[(rbA * 8 + hq) * (OT_BYTES / 16)]) + (rbw * 16 + g) * 16 + c4 * 4;
      const uint32_t kq = (sb & 0x3FFFF) >> 4, vlo = desc_lo(sb + 10240, 128), kcq = ((sb + S_KC) & 0x3FFFF) >> 4;
      const uint32_t* sched = p.sched[rbA < 2 ? rbA : 2][wg];
      auto qk_even = [&](uint32_t t) {
        wgmma_rs_n64_t0(A, qe[0], qe[1], qe[2], qe[3], desc<128, 0>(t | (128u << 16), 0), 0);
        wgmma_rs_n64_t0(A, qe[4], qe[5], z0, z1, desc<128, 0>((t + 256) | ((kcq - 256 - t) << 16), 0), 1);
      };
      auto qk_odd = [&](uint32_t t) {
        wgmma_rs_n64_t0(B, qo[0], qo[1], z2, z3, desc<128, 0>((t + 256) | ((kcq - 256 - t) << 16), 0), 0);
        wgmma_rs_n64_t0(B, qo[2], qo[3], qo[4], qo[5], desc<128, 0>((t + 384) | (128u << 16), 0), 1);
      };
      auto swapr = [&](uint32_t& a, uint32_t& b) { asm volatile("{\n.reg .b32 t;\nmov.b32 t, %0;\nmov.b32 %0, %1;\nmov.b32 %1, t;\n}" : "+r"(a), "+r"(b)); };
      auto swapf = [&](float& a, float& b) { asm volatile("{\n.reg .f32 t;\nmov.f32 t, %0;\nmov.f32 %0, %1;\nmov.f32 %1, t;\n}" : "+f"(a), "+f"(b)); };
      auto swap_pair = [&]() {
        #pragma unroll
        for (int i = 0; i < 6; i++) { swapr(qe[i], ye[i]); swapr(qo[i], yo[i]); }
        #pragma unroll
        for (int i = 0; i < 4; i++) swapr(sh[i], xh[i]);
      };
      auto probs = [&](const float (&S)[32], uint32_t (&pf)[4][4], uint32_t m0, uint32_t m1, uint32_t m2) {
        #pragma unroll
        for (int b = 0; b < 4; b++) {
          #pragma unroll
          for (int i = 0; i < 4; i++) pf[b][i] = pack2(ex2(S[8 * b + 2 * i]), ex2(S[8 * b + 2 * i + 1]));
          if (b == w) { pf[b][0] &= m0; pf[b][1] &= m1; pf[b][2] &= m2; pf[b][3] &= m0; }
        }
      };
      uint32_t bad = 0;
      auto finish = [&](const float (&O)[12], int odd, int P) {
        const int src = (lane & 28) | (odd ? 0 : 2);
        const float l0 = __shfl_sync(~0u, odd ? O[0] : O[8], src), l1 = __shfl_sync(~0u, odd ? O[2] : O[10], src);
        constexpr uint32_t LO = (127u - 60u) << 23, RANGE = 120u << 23;
        bad |= (uint32_t)(__float_as_uint(l0) - LO > RANGE) | (uint32_t)(__float_as_uint(l1) - LO > RANGE);
        const float i0 = rcp(l0), i1 = rcp(l1);
        uint8_t* o = og + (5 * P + 2 * odd) * 2048;
        #pragma unroll
        for (int i = 0; i < 3; i++) {
          if (i == 1 || (i == 0 ? (!odd || !lowq) : (odd || lowq))) {
            *reinterpret_cast<uint32_t*>(o + i * 2048) = pack2(O[4 * i] * i0, O[4 * i + 1] * i0);
            *reinterpret_cast<uint32_t*>(o + i * 2048 + 128) = pack2(O[4 * i + 2] * i1, O[4 * i + 3] * i1);
          }
        }
      };
      bool shifted = false;
      while (true) {
        #pragma unroll
        for (int i = 0; i < 12; i++) asm volatile("mov.f32 %0, 0f00000000;\nmov.f32 %1, 0f00000000;\nmov.f32 %2, 0f00000000;\nmov.f32 %3, 0f00000000;" : "=f"(Oe[i]), "=f"(Oo[i]), "=f"(Xe[i]), "=f"(Xo[i]));
        uint32_t e0 = sched[0];
        int u = 0;
        [[maybe_unused]] int seg = 0;
        #pragma unroll 1
        while (true) {
          { const uint32_t zm = zmask(e0); z0 = zm | sh[0]; z1 = zm | sh[1]; z2 = zm | sh[2]; z3 = zm | sh[3]; }
          wg_fence();
          qk_even(kq + (e0 & 0xffffu));
          wg_commit();
          wg_fence();
          qk_odd(kq + (e0 & 0xffffu));
          wg_commit();
          wg_wait<1>();
          PROF_G(0);
          #pragma unroll 1
          do {
            [[maybe_unused]] const int uu = u;
            PROF_S(0);
            const uint32_t e1 = sched[++u];
            const uint32_t kb = kq + (e1 & 0xffffu), vb = vlo + (e0 & 0xffffu), kvbar = bar(B_KVFULL + ((e1 >> 22) & 3));
            const uint32_t arrived = mbar_probe(kvbar, e1 & S_WAIT);
            const uint32_t t0 = e0 & S_MASK, f = t0 == S_FAR ? ~0u : 0u, any = (t0 == S_OWN || t0 == S_FAR) ? 0u : ~0u;
            const uint32_t m0 = (mk ^ f) | any, m1 = ~f | any, m2 = f | any, zm = zmask(e1);
            uint32_t pe[4][4], po[4][4];
            reg_fence(A);
            probs(A, pe, m0, m1, m2);
            PROF_S(1);
            wg_wait<0>();
            z0 = zm | sh[0]; z1 = zm | sh[1];
            mbar_wait_probed(kvbar, arrived, nspin);
            wg_fence();
            #pragma unroll
            for (int b = 0; b < 4; b++) wgmma_rs_n24_t1(Oe, pe[b][0], pe[b][1], pe[b][2], pe[b][3], desc<2048, 0>(vb, b * 256), 1);
            qk_even(kb);
            wg_commit();
            PROF_S(2);
            reg_fence(B);
            probs(B, po, m0, m1, m2);
            wg_wait<0>();
            z2 = zm | sh[2]; z3 = zm | sh[3];
            wg_fence();
            #pragma unroll
            for (int b = 0; b < 4; b++) wgmma_rs_n24_t1(Oo, po[b][0], po[b][1], po[b][2], po[b][3], desc<2048, 0>(vb, 6144 + b * 256), 1);
            qk_odd(kb);
            wg_commit();
            PROF_S(3);
            e0 = e1;
          } while (!(e0 & S_OSW));
          PROF_G(1);
          wg_wait<0>();
          reg_fence(Oe); reg_fence(Oo); reg_fence(A); reg_fence(B);
          if (e0 & S_END) break;
          swap_pair();
          #pragma unroll
          for (int i = 0; i < 12; i++) { swapf(Oe[i], Xe[i]); swapf(Oo[i], Xo[i]); }
          PROF_G(2);
          seg++;
        }
        #pragma unroll 1
        for (int P = 0; P < 2; P++) {
          finish(Oe, 0, P); finish(Oo, 1, P);
          #pragma unroll
          for (int i = 0; i < 12; i++) { swapf(Oe[i], Xe[i]); swapf(Oo[i], Xo[i]); }
        }
        PROF_G(2);
        if (shifted) break;
        uint32_t redo;
        asm volatile("{\n.reg .pred p, q;\nsetp.ne.u32 q, %1, 0;\nbar.red.or.pred p, %2, 128, q;\nselp.u32 %0, 1, 0, p;\n}" : "=r"(redo) : "r"(bad), "r"(2 + wg) : "memory");
        if (!__shfl_sync(~0u, redo, 0)) break;
        shifted = true;
        z0 = z1 = z2 = z3 = 0u;
        #pragma unroll 1
        for (int P = 0; P < 2; P++) {
          float me0 = -INFINITY, me1 = -INFINITY, mo0 = -INFINITY, mo1 = -INFINITY;
          #pragma unroll 1
          for (int u = 0; u < 10; u++) {
            const uint32_t e = sched[u];
            if ((e & S_MASK) == S_MASK || ((e & S_CUR) != 0) != (P != 0)) continue;
            asm volatile("" : "+r"(z0), "+r"(z1), "+r"(z2), "+r"(z3));
            wg_fence();
            qk_even(kq + (e & 0xffffu));
            qk_odd(kq + (e & 0xffffu));
            wg_commit();
            wg_wait<0>();
            reg_fence(A); reg_fence(B);
            const bool msk = e & S_MASK, far = (e & S_MASK) == S_FAR;
            const int k0 = 2 * c4 <= g, k1 = 2 * c4 + 1 <= g;
            #pragma unroll
            for (int b = 0; b < 4; b++) {
              const bool pa = !msk || (w + k0 > b) != far, pb = !msk || (w + k1 > b) != far, pc = !msk || (w >= b) != far, pd = !msk || (w > b) != far;
              const float* a = &A[8 * b];
              const float* o = &B[8 * b];
              if (pa) { me0 = fmaxf(me0, a[0]); me1 = fmaxf(me1, a[6]); mo0 = fmaxf(mo0, o[0]); mo1 = fmaxf(mo1, o[6]); }
              if (pb) { me0 = fmaxf(me0, a[1]); me1 = fmaxf(me1, a[7]); mo0 = fmaxf(mo0, o[1]); mo1 = fmaxf(mo1, o[7]); }
              if (pc) { me1 = fmaxf(me1, fmaxf(a[2], a[3])); mo1 = fmaxf(mo1, fmaxf(o[2], o[3])); }
              if (pd) { me0 = fmaxf(me0, fmaxf(a[4], a[5])); mo0 = fmaxf(mo0, fmaxf(o[4], o[5])); }
            }
          }
          auto split = [&](float m) {
            m = -quad_max(m);
            const uint32_t h = pack2(m, 0.f) & 0xffffu;
            const float r = m - bf_lo(h);
            const uint32_t d = pack2(r, 0.f) & 0xffffu;
            return c4 == 0 ? h | (d << 16) : c4 == 1 ? pack2(r - bf_lo(d), 0.f) & 0xffffu : 0u;
          };
          sh[0] = split(me0); sh[1] = split(me1); sh[2] = split(mo0); sh[3] = split(mo1);
          swap_pair();
        }
      }
      release_pair(B_ATTDONE);
      if (tid == 0) PROF_T(7);
      __syncwarp();
      if (lane == 0) red_release(&p.scr->flags[FL_O + rbA * 8 + hq], 1u);
      if (tid == 0) PROF_T(8);
    }
    const int r0 = warp * 16 + g;
    const uint32_t stsm_row = (uint32_t)(warp * 16 + ((lane >> 3) & 1) * 8 + (lane & 7)) * 16 + (uint32_t)(lane >> 4) * 2048;
    uint32_t hr[10][2];
    {
      const __nv_bfloat16* xp = p.x + (size_t)(rbC * 128 + r0) * DM + 80 * j + 2 * c4;
      #pragma unroll
      for (int t = 0; t < 10; t++) { hr[t][0] = ldg_u32(xp + 8 * t); hr[t][1] = ldg_u32(xp + 8 * DM + 8 * t); }
      float acc[40];
      const uint32_t alo = desc_lo(sb + wg * 1024, 2048), blo = desc_lo(sb, 4096);
      mbar_wait(bar(B_WOFULL), 0, nspin);
      #pragma unroll 1
      for (int t = 0; t < 8; t++) {
        const int s = t < 5 ? t : t - 5;
        mbar_wait(bar(B_CFULL + s), t >= 5, nspin);
        if (t == 6) mbar_wait(bar(B_WO4), 0, nspin);
        if (t == 0 && tid == 0) PROF_T(9);
        const uint32_t a = alo + s * (OT_BYTES >> 4);
        wg_fence();
        #pragma unroll
        for (int ks = 0; ks < 5; ks++) {
          const int k = 80 * t + 16 * ks;
          const uint32_t b = blo + (k >= 512 ? WO4_OFF >> 4 : (WO_OFF >> 4) + (k >> 7) * 1280) + (k & 127) * 2;
          wgmma_ss_n80_t1(acc, desc<128, 0>(a, ks * 4096), desc<256, 3>(b, 0), (t > 0 || ks > 0) ? 1 : 0);
        }
        wg_commit();
        wg_wait<1>();
        if (t >= 1 && t <= 3) release_pair(B_CEMPTY + t - 1);
      }
      wg_wait<0>();
      reg_fence(acc);
      release_pair(B_CDONE);
      if (tid == 0) PROF_T(10);
      named_sync(1, 256);
      float s0 = 0.f, q0 = 0.f, s1 = 0.f, q1 = 0.f;
      #pragma unroll
      for (int i = 0; i < 5; i++) {
        #pragma unroll
        for (int u = 0; u < 2; u++) {
          const int t = 2 * i + u;
          hr[t][0] = pack2(acc[4 * t] + bf_lo(hr[t][0]), acc[4 * t + 1] + bf_hi(hr[t][0]));
          hr[t][1] = pack2(acc[4 * t + 2] + bf_lo(hr[t][1]), acc[4 * t + 3] + bf_hi(hr[t][1]));
          const float a = bf_lo(hr[t][0]), b = bf_hi(hr[t][0]), c = bf_lo(hr[t][1]), d = bf_hi(hr[t][1]);
          s0 += a + b; q0 = fmaf(a, a, fmaf(b, b, q0)); s1 += c + d; q1 = fmaf(c, c, fmaf(d, d, q1));
        }
        stsm4(sb + i * 4096 + stsm_row, hr[2 * i][0], hr[2 * i][1], hr[2 * i + 1][0], hr[2 * i + 1][1]);
      }
      s0 = quad_sum(s0); q0 = quad_sum(q0); s1 = quad_sum(s1); q1 = quad_sum(q1);
      if (c4 == 0) { sts_f2(sb + 20480 + r0 * 8, s0, q0); sts_f2(sb + 20480 + (r0 + 8) * 8, s1, q1); }
      fence_async();
      __syncwarp();
      if (lane == 0) mbar_arrive(bar(B_HW));
      if (tid == 0) PROF_T(11);
    }
    {
      float acc[96];
      float hs0 = 0.f, hq0 = 0.f, hs1 = 0.f, hq1 = 0.f;
      const uint32_t alo = desc_lo(sb + wg * 1024, 2048), blo = desc_lo(sb + DB_OFF, 10240);
      #pragma unroll 1
      for (int t = 0; t < 8; t++) {
        const int s = t & 3;
        mbar_wait(bar(B_DBFULL + s), t >> 2, nspin);
        mbar_wait(bar(B_DAFULL + s), t >> 2, nspin);
        if (t == 0 && tid == 0) PROF_T(12);
        if (t == 2 && tid == 0) PROF_T(13);
        const uint32_t a = alo + s * (HT_BYTES >> 4), b = blo + s * (DB_SLOT >> 4);
        wg_fence();
        #pragma unroll
        for (int ks = 0; ks < 5; ks++)
          wgmma_ss_n192_t1(acc, desc<128, 0>(a, ks * 4096), desc<1024, 1>(b, ks * 2048), (t > 0 || ks > 0) ? 1 : 0);
        wg_commit();
        const float2 u0 = lds_f2(sb + s * HT_BYTES + 20480 + r0 * 8), u1 = lds_f2(sb + s * HT_BYTES + 20480 + (r0 + 8) * 8);
        hs0 += u0.x; hq0 += u0.y; hs1 += u1.x; hq1 += u1.y;
        wg_wait<1>();
        if (t > 0) { release_pair(B_DAEMPTY + ((t - 1) & 3)); if ((tid & 127) == 0) mbar_arrive(bar(B_DBEMPTY + ((t - 1) & 3))); }
      }
      wg_wait<0>();
      reg_fence(acc);
      if ((tid & 127) == 0) mbar_arrive(bar(B_DBEMPTY + 3));
      release_pair(B_DDONE);
      if (tid == 0) PROF_T(14);
      const float mu0 = hs0 * (1.f / DM), mu1 = hs1 * (1.f / DM);
      const float rs0 = rsq(fmaxf(hq0 * (1.f / DM) - mu0 * mu0, 0.f) + 1e-5f), rs1 = rsq(fmaxf(hq1 * (1.f / DM) - mu1 * mu1, 0.f) + 1e-5f);
      const float mr0 = -mu0 * rs0, mr1 = -mu1 * rs1;
      mbar_wait(bar(B_CS2), 0, nspin);
      named_sync(1, 256);
      #pragma unroll
      for (int i = 0; i < 12; i++) {
        uint32_t r[4];
        #pragma unroll
        for (int u = 0; u < 2; u++) {
          const int t = 2 * i + u;
          const float4 cb = lds_f4(sb + S_CS2 + (8 * t + 2 * c4) * 8);
          r[2 * u] = sq2(pack2_relu(fmaf(acc[4 * t], rs0, fmaf(cb.x, mr0, cb.y)), fmaf(acc[4 * t + 1], rs0, fmaf(cb.z, mr0, cb.w))));
          r[2 * u + 1] = sq2(pack2_relu(fmaf(acc[4 * t + 2], rs1, fmaf(cb.x, mr1, cb.y)), fmaf(acc[4 * t + 3], rs1, fmaf(cb.z, mr1, cb.w))));
        }
        stsm4(sb + rank * 49152 + i * 4096 + stsm_row, r[0], r[1], r[2], r[3]);
      }
      fence_async();
      __syncwarp();
      if (lane == 0) mbar_arrive(bar(B_FW));
      named_sync(2 + wg, 128);
      if (tid == 0) PROF_T(15);
    }
    {
      float acc1[96], acm[32], acr[32];
      const unsigned tag = lds_u32(sb + S_EPOCH);
      const uint32_t alo = desc_lo(sb + wg * 1024, 2048), blo = desc_lo(sb + EB_OFF, 8192), rlo = desc_lo(sb + EB_OFF + 8192, 2048);
      uint4* pbase = &p.scr->part[(size_t)((rbC * 2 + rank) * 16) * (8 * 5 * 32) + warp * 160 + lane];
      unsigned* fbase = &p.scr->flags[FL_P + ((rbC * 2 + rank) * 2 * 8 + warp) * 4];
      #pragma unroll 1
      for (int i = 0; i < 6; i++) {
        const int s = i % 5;
        mbar_wait(bar(B_EBFULL + s), i / 5, nspin);
        if (i >= 3) mbar_wait(bar(B_FFULL + i - 3), 0, nspin);
        const uint32_t a = alo + (i < 3 ? rank * 3072 + i * 1024 : (rank ^ 1) * 3072 + (i - 3) * 1024), b = blo + s * (EB_SLOT >> 4);
        wg_fence();
        #pragma unroll
        for (int ks = 0; ks < 4; ks++)
          wgmma_ss_n192_t1(acc1, desc<128, 0>(a, ks * 4096), desc<1024, 1>(b, ks * 2048), (i > 0 || ks > 0) ? 1 : 0);
        wg_commit();
        wg_wait<1>();
        if (i > 0 && (tid & 127) == 0) mbar_arrive(bar(B_EBEMPTY + (i - 1) % 5));
      }
      if (tid == 0) PROF_T(16);
      auto pass2_step = [&](int i) {
        const int s = i % 5;
        mbar_wait(bar(B_EBFULL + s), (i / 5) & 1, nspin);
        const int ks0 = i - 6;
        const uint32_t a = alo + (ks0 < 3 ? rank * 3072 + ks0 * 1024 : (rank ^ 1) * 3072 + (ks0 - 3) * 1024), so = s * (EB_SLOT >> 4);
        wg_fence();
        #pragma unroll
        for (int ks = 0; ks < 4; ks++) {
          const int sc = (i > 6 || ks > 0) ? 1 : 0;
          wgmma_ss_n64_t1(acm, desc<128, 0>(a, ks * 4096), desc<1024, 1>(blo + so, ks * 2048), sc);
          wgmma_ss_n64_t1(acr, desc<128, 0>(a, ks * 4096), desc<256, 3>(rlo + so, ks * 512), sc);
        }
        wg_commit();
        wg_wait<1>();
        if ((tid & 127) == 0) mbar_arrive(bar(B_EBEMPTY + (i - 1) % 5));
      };
      pass2_step(6);
      {
        reg_fence(acc1);
        #pragma unroll
        for (int q = 0; q < 3; q++) {
          uint4* d = pbase + (((jj + 1 + q) & 3) * 4 + jj) * 1280;
          #pragma unroll
          for (int u = 0; u < 4; u++) {
            const float* a1 = &acc1[32 * q + 8 * u];
            d[u * 32] = make_uint4(pack2(a1[0], a1[1]), pack2(a1[2], a1[3]), pack2(a1[4], a1[5]), pack2(a1[6], a1[7]));
          }
        }
        __syncwarp();
        if (lane == 0) st_release(fbase + jj, tag);
      }
      #pragma unroll 1
      for (int i = 7; i < 12; i++) pass2_step(i);
      wg_wait<0>();
      reg_fence(acm); reg_fence(acr);
      if (tid == 0) PROF_T(17);
      #pragma unroll
      for (int q = 0; q < 3; q++) {
        const float* a1 = &acr[8 * q];
        pbase[(((jj + 1 + q) & 3) * 4 + jj) * 1280 + 128] = make_uint4(pack2(a1[0], a1[1]), pack2(a1[2], a1[3]), pack2(a1[4], a1[5]), pack2(a1[6], a1[7]));
      }
      __syncwarp();
      if (lane == 0) st_release(fbase + 32 + jj, tag);
      const __nv_bfloat16* b2p = p.b2 + 80 * j + 2 * c4;
      float k[40];
      #pragma unroll
      for (int t = 0; t < 10; t++) {
        const uint32_t bb = ldg_u32(b2p + 8 * t);
        const float* a1 = t < 8 ? &acm[4 * t] : &acr[24 + 4 * (t - 8)];
        k[4 * t] = a1[0] + bf_lo(bb) + bf_lo(hr[t][0]); k[4 * t + 1] = a1[1] + bf_hi(bb) + bf_hi(hr[t][0]);
        k[4 * t + 2] = a1[2] + bf_lo(bb) + bf_lo(hr[t][1]); k[4 * t + 3] = a1[3] + bf_hi(bb) + bf_hi(hr[t][1]);
      }
      __nv_bfloat16* op = p.out + (size_t)(rbC * 128 + r0) * DM + 80 * j + 2 * c4;
      #pragma unroll
      for (int pass = 0; pass < 2; pass++) {
        while (++nspin < SPIN_LIMIT) {
          const unsigned v = ld_relaxed(fbase + pass * 32 + (lane & 3));
          if (__all_sync(~0u, (lane & 3) == jj || (int)(v - tag) >= 0)) break;
        }
        #pragma unroll
        for (int d = 1; d < 4; d++) {
          const uint4* src = pbase + (jj * 4 + ((jj + d) & 3)) * 1280;
          #pragma unroll
          for (int u = (pass ? 4 : 0); u < (pass ? 5 : 4); u++) {
            const uint4 v = ldg_cg_u4(src + u * 32);
            float* kk = &k[8 * u];
            kk[0] += bf_lo(v.x); kk[1] += bf_hi(v.x); kk[2] += bf_lo(v.y); kk[3] += bf_hi(v.y);
            kk[4] += bf_lo(v.z); kk[5] += bf_hi(v.z); kk[6] += bf_lo(v.w); kk[7] += bf_hi(v.w);
          }
        }
        #pragma unroll
        for (int t = (pass ? 8 : 0); t < (pass ? 10 : 8); t++) {
          *reinterpret_cast<uint32_t*>(op + 8 * t) = pack2(k[4 * t], k[4 * t + 1]);
          *reinterpret_cast<uint32_t*>(op + 8 * DM + 8 * t) = pack2(k[4 * t + 2], k[4 * t + 3]);
        }
      }
      if (tid == 0) PROF_T(18);
    }
  }
  __syncwarp();
  cluster_arrive();
  cluster_wait();
}

typedef CUresult (*EncodeTiledFn)(CUtensorMap*, CUtensorMapDataType, cuuint32_t, void*, const cuuint64_t*, const cuuint64_t*, const cuuint32_t*,
                                  const cuuint32_t*, CUtensorMapInterleave, CUtensorMapSwizzle, CUtensorMapL2promotion, CUtensorMapFloatOOBfill);

static bool encode_map(EncodeTiledFn fn, CUtensorMap* m, const void* ptr, int rank, const cuuint64_t* dims, const cuuint64_t* strides, const cuuint32_t* box,
                       CUtensorMapSwizzle sw) {
  const cuuint32_t es[3] = {1, 1, 1};
  return fn(m, CU_TENSOR_MAP_DATA_TYPE_BFLOAT16, rank, const_cast<void*>(ptr), dims, strides, box, es, CU_TENSOR_MAP_INTERLEAVE_NONE, sw,
            CU_TENSOR_MAP_L2_PROMOTION_L2_256B, CU_TENSOR_MAP_FLOAT_OOB_FILL_NONE) == CUDA_SUCCESS;
}

static void attention_schedule(Params& p) {
  for (int cls = 0; cls < 3; cls++)
    for (int wg = 0; wg < 2; wg++) {
      uint32_t* s = p.sched[cls][wg];
      int n = 0;
      auto add = [&](int P, int st, bool d, uint32_t fl) {
        const bool valid = st <= cls;
        const uint32_t base = !valid || st == 0 ? KV_OWN : st == 1 ? KV_PREV : KV_FAR;
        uint32_t e = ((base + P * KV_HALF + (d ? wg : 1 - wg) * 1024) >> 4) | fl | (P ? S_CUR : 0u);
        e |= !valid ? S_MASK : !d || st == 1 ? 0u : st == 0 ? S_OWN : S_FAR;
        if (valid && st > 0 && d) e |= S_WAIT | ((uint32_t)((st - 1) + 2 * (1 - P)) << 22);
        s[n++] = e;
      };
      for (int P = 0; P < 2; P++) { add(P, 0, true, P ? S_OSW : 0u); if (wg == 1) add(P, 0, false, 0u); }
      for (int P = 1; P >= 0; P--) {
        add(P, 1, true, P ? 0u : S_OSW); add(P, 1, false, 0u); add(P, 2, true, 0u);
        if (wg == 0) add(P, 2, false, 0u);
      }
      s[n++] = (KV_OWN >> 4) | S_OSW | S_END;
      s[n++] = KV_OWN >> 4;
    }
}

}

extern "C" void kernel_launch(void* const* d_in, const int* in_sizes, int n_in, void* d_out, int out_size) {
  using namespace blk;
  (void)in_sizes; (void)n_in; (void)out_size;
  static EncodeTiledFn encode = nullptr;
  static void* scratch = nullptr;
  if (!encode) {
    cudaDriverEntryPointQueryResult st;
    void* fn = nullptr;
    if (cudaGetDriverEntryPoint("cuTensorMapEncodeTiled", &fn, cudaEnableDefault, &st) != cudaSuccess || !fn) return;
    encode = reinterpret_cast<EncodeTiledFn>(fn);
    cudaFuncSetAttribute(fused_block_kernel, cudaFuncAttributeMaxDynamicSharedMemorySize, SMEM_BYTES);
    cudaGetSymbolAddress(&scratch, g_scr);
  }
  Params p;
  p.x = static_cast<const __nv_bfloat16*>(d_in[0]); p.wqkv = static_cast<const __nv_bfloat16*>(d_in[1]); p.wo = static_cast<const __nv_bfloat16*>(d_in[2]);
  p.w1 = static_cast<const __nv_bfloat16*>(d_in[4]); p.b1 = static_cast<const __nv_bfloat16*>(d_in[5]);
  p.w2 = static_cast<const __nv_bfloat16*>(d_in[6]); p.b2 = static_cast<const __nv_bfloat16*>(d_in[7]); p.out = static_cast<__nv_bfloat16*>(d_out);
  p.scr = static_cast<Scratch*>(scratch);
  attention_schedule(p);
  CUtensorMap mX, mWq, mWr, mWo, mW1, mW2, mW2r;
  bool ok = true;
  { cuuint64_t d[2] = {DM, SEQ}, s[1] = {DM * 2}; cuuint32_t b[2] = {64, 128}; ok &= encode_map(encode, &mX, p.x, 2, d, s, b, CU_TENSOR_MAP_SWIZZLE_128B); }
  { cuuint64_t d[3] = {DM, DM, 3}, s[2] = {3 * DM * 2, DM * 2}; cuuint32_t b[3] = {64, 32, 3}; ok &= encode_map(encode, &mWq, p.wqkv, 3, d, s, b, CU_TENSOR_MAP_SWIZZLE_128B); }
  { cuuint64_t d[3] = {DM, DM, 3}, s[2] = {3 * DM * 2, DM * 2}; cuuint32_t b[3] = {16, 32, 3}; ok &= encode_map(encode, &mWr, p.wqkv, 3, d, s, b, CU_TENSOR_MAP_SWIZZLE_32B); }
  { cuuint64_t d[3] = {16, DM, DM / 16}, s[2] = {DM * 2, 32}; cuuint32_t b[3] = {16, 128, 5}; ok &= encode_map(encode, &mWo, p.wo, 3, d, s, b, CU_TENSOR_MAP_SWIZZLE_32B); }
  { cuuint64_t d[2] = {FF, DM}, s[1] = {FF * 2}; cuuint32_t b[2] = {64, 80}; ok &= encode_map(encode, &mW1, p.w1, 2, d, s, b, CU_TENSOR_MAP_SWIZZLE_128B); }
  { cuuint64_t d[2] = {DM, FF}, s[1] = {DM * 2}; cuuint32_t b[2] = {64, 64}; ok &= encode_map(encode, &mW2, p.w2, 2, d, s, b, CU_TENSOR_MAP_SWIZZLE_128B); }
  { cuuint64_t d[2] = {DM, FF}, s[1] = {DM * 2}; cuuint32_t b[2] = {16, 64}; ok &= encode_map(encode, &mW2r, p.w2, 2, d, s, b, CU_TENSOR_MAP_SWIZZLE_32B); }
  if (!ok) return;
  cudaLaunchConfig_t cfg = {};
  cfg.gridDim = dim3(NCTA); cfg.blockDim = dim3(384); cfg.dynamicSmemBytes = SMEM_BYTES; cfg.stream = cudaStreamPerThread;
  cudaLaunchAttribute at[1];
  at[0].id = cudaLaunchAttributeClusterDimension; at[0].val.clusterDim.x = 2; at[0].val.clusterDim.y = 1; at[0].val.clusterDim.z = 1;
  cfg.attrs = at; cfg.numAttrs = 1;
  cudaLaunchKernelEx(&cfg, fused_block_kernel, mX, mWq, mWr, mWo, mW1, mW2, mW2r, p);
}
```

```cpp
#include <cuda_runtime.h>
#include <cuda.h>
#include <cuda_bf16.h>
#include <stdint.h>

namespace blk {

constexpr int SEQ = 2048, DM = 640, FF = 1536;
constexpr int NCTA = 128;
constexpr int PRE_N = 2;
constexpr unsigned SLOW_NS = 500, KV_NS = 100;

constexpr uint32_t A_STAGE = 47104;
constexpr uint32_t CS_STG0 = 188416, CS_STG1 = 217088;
constexpr uint32_t KV_HALF = 22528, KV_BLK = 45056;
constexpr uint32_t KV_PAIR = 3 * KV_HALF;
__host__ __device__ constexpr uint32_t kv_off(uint32_t P, uint32_t back) { return P * KV_PAIR + (2 - back) * KV_HALF; }
constexpr uint32_t OT_BYTES = 20480, OT_HALF = 10240;
__host__ __device__ constexpr uint32_t ot_off(uint32_t s) { return s < 3 ? KV_PAIR + s * OT_BYTES : 2 * KV_PAIR; }
constexpr uint32_t WO_BYTES = 12800;
constexpr uint32_t WOE_OFF = 165888, WOL_OFF = 0;
constexpr uint32_t XR_OFF = ot_off(3), XR1_OFF = XR_OFF + 16384;
constexpr uint32_t HT_BYTES = 21504;
constexpr uint32_t DB_OFF = 98304, DB_SLOT = 30720;
constexpr uint32_t EB_OFF = 98304, EB_SLOT = 24576;
__host__ __device__ constexpr uint32_t db_off(uint32_t s) { return DB_OFF + ((s + 2) & 3) * DB_SLOT; }
__host__ __device__ constexpr uint32_t eb_off(uint32_t s) { return EB_OFF + (s < 2 ? s + 3 : s - 2) * EB_SLOT; }
constexpr uint32_t AUX = 225280;
constexpr uint32_t BARS = AUX;
constexpr uint32_t S_CS1 = AUX + 512;
constexpr uint32_t S_CS2 = AUX + 2560;
constexpr uint32_t S_PART = AUX + 2432;
constexpr uint32_t BARS2 = AUX + 4096 + 64;
constexpr uint32_t S_KC = AUX + 4096 + 256;
constexpr uint32_t SMEM_BYTES = S_KC + 1024;

enum Bar : int {
  B_AFULL = 0  , B_AEMPTY = 4  ,
  B_STAT = 8, B_KVFULL = 9  , B_KVST = 13, B_AUXDONE = 14, B_WOFULL = 15, B_WOL = 16  , B_OST = 20, B_DAFULL = 22  , B_DBFULL = 26  ,
  B_FFULL = 30  , B_EBFULL = 33  , B_CS2 = 38, B_XR = 39, B_AUX2 = 40,
  B_DBEMPTY = 41  , B_EBEMPTY = 45  , B_KVW = 50  , B_HW = 52, B_FW = 53, B_DAEMPTY = 54  , B_CEMPTY = 58  ,
  B_CDONE = 62, B_DDONE = 63, B_COUNT = 64,
  B_PF = 520  , B_ST = 521  , B_P1D = 532  , B_OW = 533  , B_CFULL = 535  , B_A0 = 539
};
static_assert(BARS + 520 * 8 == BARS2, "barrier map");
__device__ __forceinline__ uint32_t bar_count(int i) { return i < B_DBEMPTY ? 1 : i < B_KVW ? 2 : i < B_DAEMPTY ? 8 : 4; }

constexpr int FL_EPOCH = 0, FL_I = 128, FL_CTA = 256, FW_H = 0, FW_O = 8  , FW_KV = 24;
struct Scratch {
  uint4 kv[128 * (KV_BLK / 16)];
  uint4 o[128 * (OT_BYTES / 16)];
  uint4 h[128 * (HT_BYTES / 16)];
  uint4 wo[64 * (WO_BYTES / 16)];
  unsigned long long cs[3 * DM + FF];
  unsigned flags[FL_CTA + 128 * 32];
};
__device__ __align__(1024) Scratch g_scr;

__device__ __forceinline__ uint32_t smem_u32(const void* p) { return (uint32_t)__cvta_generic_to_shared(p); }
__device__ __forceinline__ void mbar_init(uint32_t bar, uint32_t cnt) { asm volatile("mbarrier.init.shared::cta.b64 [%0], %1;" :: "r"(bar), "r"(cnt)); }
__device__ __forceinline__ void mbar_expect_tx(uint32_t bar, uint32_t bytes) { asm volatile("mbarrier.arrive.expect_tx.shared::cta.b64 _, [%0], %1;" :: "r"(bar), "r"(bytes) : "memory"); }
__device__ __forceinline__ void mbar_arrive(uint32_t bar) { asm volatile("mbarrier.arrive.shared::cta.b64 _, [%0];" :: "r"(bar) : "memory"); }
__device__ __forceinline__ uint32_t mapa(uint32_t addr, uint32_t cta) { uint32_t r; asm volatile("mapa.shared::cluster.u32 %0, %1, %2;" : "=r"(r) : "r"(addr), "r"(cta)); return r; }
__device__ __forceinline__ void mbar_arrive_cluster(uint32_t bar, uint32_t cta) {
  asm volatile("{\n.reg .b32 ra;\nmapa.shared::cluster.u32 ra, %0, %1;\nmbarrier.arrive.shared::cluster.b64 _, [ra];\n}" :: "r"(bar), "r"(cta) : "memory");
}
constexpr unsigned SPIN_LIMIT = 1u << 22;
__device__ __forceinline__ void mbar_wait(uint32_t bar, uint32_t parity, unsigned& n) {
  asm volatile("{\n.reg .pred p, q;\nmbarrier.try_wait.parity.shared::cta.b64 p, [%1], %2;\n@p bra DONE_%=;\n"
               "WAIT_%=:\nmbarrier.try_wait.parity.shared::cta.b64 p, [%1], %2;\n@!p add.u32 %0, %0, 1;\n"
               "setp.lt.and.u32 q, %0, %3, !p;\n@q bra WAIT_%=;\nDONE_%=:\n}" : "+&r"(n) : "r"(bar), "r"(parity), "n"(SPIN_LIMIT) : "memory");
}
__device__ __forceinline__ uint32_t mbar_probe(uint32_t bar, uint32_t need) {
  uint32_t ok;
  asm volatile("{\n.reg .pred p;\nsetp.eq.u32 p, %2, 0;\n@!p mbarrier.test_wait.parity.shared::cta.b64 p, [%1], 0;\nselp.u32 %0, 1, 0, p;\n}" : "=r"(ok) : "r"(bar), "r"(need) : "memory");
  return ok;
}
__device__ __forceinline__ void mbar_wait_probed(uint32_t bar, uint32_t ok, unsigned& n) {
  asm volatile("{\n.reg .pred p, q;\nsetp.ne.u32 p, %2, 0;\n@p bra DONE_%=;\nWAIT_%=:\nmbarrier.try_wait.parity.shared::cta.b64 p, [%1], 0;\n@!p add.u32 %0, %0, 1;\n"
               "setp.lt.and.u32 q, %0, %3, !p;\n@q bra WAIT_%=;\nDONE_%=:\n}" : "+&r"(n) : "r"(bar), "r"(ok), "n"(SPIN_LIMIT) : "memory");
}
__device__ __forceinline__ unsigned ld_relaxed(const unsigned* p) { unsigned v; asm volatile("ld.relaxed.gpu.global.u32 %0, [%1];" : "=r"(v) : "l"(p) : "memory"); return v; }
__device__ __forceinline__ unsigned ld_acquire(const unsigned* p) { unsigned v; asm volatile("ld.acquire.gpu.global.u32 %0, [%1];" : "=r"(v) : "l"(p) : "memory"); return v; }
__device__ __forceinline__ void st_relaxed(unsigned* p, unsigned v) { asm volatile("st.relaxed.gpu.global.u32 [%0], %1;" :: "l"(p), "r"(v) : "memory"); }
__device__ __forceinline__ void st_relaxed64(unsigned long long* p, unsigned lo, unsigned hi) {
  asm volatile("{\n.reg .b64 v;\nmov.b64 v, {%1, %2};\nst.relaxed.gpu.global.u64 [%0], v;\n}" :: "l"(p), "r"(lo), "r"(hi) : "memory");
}
__device__ __forceinline__ void st_release(unsigned* p, unsigned v) { asm volatile("st.release.gpu.global.u32 [%0], %1;" :: "l"(p), "r"(v) : "memory"); }
__device__ __forceinline__ void fence_acq() { asm volatile("fence.acq_rel.gpu;" ::: "memory"); }
__device__ __forceinline__ void fence_async() { asm volatile("fence.proxy.async.shared::cta;" ::: "memory"); }
__device__ __forceinline__ void fence_async_global() { asm volatile("fence.proxy.async.global;" ::: "memory"); }
__device__ __forceinline__ bool elect_one() {
  uint32_t r;
  asm volatile("{\n.reg .pred P;\nelect.sync _|P, 0xffffffff;\nselp.u32 %0, 1, 0, P;\n}" : "=r"(r));
  return r != 0;
}
template <unsigned NS = 0> __device__ __forceinline__ void wait_flag(const unsigned* p, unsigned target, unsigned& n) {
  if ((int)(ld_acquire(p) - target) >= 0) return;
  do { if (NS) __nanosleep(NS); } while ((int)(ld_acquire(p) - target) < 0 && ++n < SPIN_LIMIT);
}
__device__ __forceinline__ void tma_2d(uint32_t dst, const CUtensorMap* map, int c0, int c1, uint32_t bar) {
  asm volatile("cp.async.bulk.tensor.2d.shared::cluster.global.mbarrier::complete_tx::bytes [%0], [%1, {%3, %4}], [%2];"
    :: "r"(dst), "l"(map), "r"(bar), "r"(c0), "r"(c1) : "memory");
}
__device__ __forceinline__ void tma_3d(uint32_t dst, const CUtensorMap* map, int c0, int c1, int c2, uint32_t bar) {
  asm volatile("cp.async.bulk.tensor.3d.shared::cluster.global.mbarrier::complete_tx::bytes [%0], [%1, {%3, %4, %5}], [%2];"
    :: "r"(dst), "l"(map), "r"(bar), "r"(c0), "r"(c1), "r"(c2) : "memory");
}
__device__ __forceinline__ void tma_3d_mc(uint32_t dst, const CUtensorMap* map, int c0, int c1, int c2, uint32_t bar) {
  asm volatile("cp.async.bulk.tensor.3d.shared::cluster.global.mbarrier::complete_tx::bytes.multicast::cluster [%0], [%1, {%3, %4, %5}], [%2], %6;"
    :: "r"(dst), "l"(map), "r"(bar), "r"(c0), "r"(c1), "r"(c2), "h"((uint16_t)3) : "memory");
}
__device__ __forceinline__ void bulk_ld(uint32_t dst, const void* src, uint32_t bytes, uint32_t bar) {
  asm volatile("cp.async.bulk.shared::cluster.global.mbarrier::complete_tx::bytes [%0], [%1], %2, [%3];" :: "r"(dst), "l"(src), "r"(bytes), "r"(bar) : "memory");
}
__device__ __forceinline__ void bulk_ld_mc(uint32_t dst, const void* src, uint32_t bytes, uint32_t bar) {
  asm volatile("cp.async.bulk.shared::cluster.global.mbarrier::complete_tx::bytes.multicast::cluster [%0], [%1], %2, [%3], %4;"
    :: "r"(dst), "l"(src), "r"(bytes), "r"(bar), "h"((uint16_t)3) : "memory");
}
__device__ __forceinline__ void bulk_st(void* dst, uint32_t src, uint32_t bytes) {
  asm volatile("cp.async.bulk.global.shared::cta.bulk_group [%0], [%1], %2;" :: "l"(dst), "r"(src), "r"(bytes) : "memory");
}
__device__ __forceinline__ void bulk_dsmem(uint32_t rdst, uint32_t src, uint32_t bytes, uint32_t rbar) {
  asm volatile("cp.async.bulk.shared::cluster.shared::cta.mbarrier::complete_tx::bytes [%0], [%1], %2, [%3];" :: "r"(rdst), "r"(src), "r"(bytes), "r"(rbar) : "memory");
}
__device__ __forceinline__ void tma_red_add(const CUtensorMap* map, uint32_t src, int c0, int c1) {
  asm volatile("cp.reduce.async.bulk.tensor.2d.global.shared::cta.add.tile.bulk_group [%0, {%2, %3}], [%1];" :: "l"(map), "r"(src), "r"(c0), "r"(c1) : "memory");
}
__device__ __forceinline__ void bulk_wait_read0() { asm volatile("cp.async.bulk.wait_group.read 0;" ::: "memory"); }
__device__ __forceinline__ void bulk_commit() { asm volatile("cp.async.bulk.commit_group;" ::: "memory"); }
__device__ __forceinline__ void bulk_wait0() { asm volatile("cp.async.bulk.wait_group 0;" ::: "memory"); }
__device__ __forceinline__ void prefetch_l2(const void* p, uint32_t bytes) { asm volatile("cp.async.bulk.prefetch.L2.global [%0], %1;" :: "l"(p), "r"(bytes) : "memory"); }
__device__ __forceinline__ void prefetch_map(const CUtensorMap* m) { asm volatile("prefetch.tensormap [%0];" :: "l"(m) : "memory"); }
__device__ __forceinline__ void cp_async16(uint32_t dst, const void* src) { asm volatile("cp.async.cg.shared.global.L2::128B [%0], [%1], 16;" :: "r"(dst), "l"(src) : "memory"); }
__device__ __forceinline__ void cp_async_wait_all() { asm volatile("cp.async.wait_all;" ::: "memory"); }
__device__ __forceinline__ void cluster_arrive() { asm volatile("barrier.cluster.arrive.relaxed.aligned;" ::: "memory"); }
__device__ __forceinline__ void cluster_wait() { asm volatile("barrier.cluster.wait.acquire.aligned;" ::: "memory"); }
__device__ __forceinline__ void named_sync(int id, int n) { asm volatile("bar.sync %0, %1;" :: "r"(id), "r"(n) : "memory"); }
__device__ __forceinline__ void wg_fence() { asm volatile("wgmma.fence.sync.aligned;" ::: "memory"); }
__device__ __forceinline__ void wg_commit() { asm volatile("wgmma.commit_group.sync.aligned;" ::: "memory"); }
template <int N> __device__ __forceinline__ void wg_wait() { asm volatile("wgmma.wait_group.sync.aligned %0;" :: "n"(N) : "memory"); }
template <int N> __device__ __forceinline__ void reg_fence(float (&d)[N]) {
  #pragma unroll
  for (int i = 0; i < N; i++) asm volatile("" : "+f"(d[i]) :: "memory");
}
constexpr uint32_t SB0 = 1024;
__device__ __forceinline__ uint32_t desc_lo(uint32_t off, uint32_t lbo) { return ((SB0 + off) >> 4) | ((lbo >> 4) << 16); }
template <uint32_t SBO, uint32_t SWZ> __device__ __forceinline__ uint64_t desc(uint32_t lo, uint32_t byte_off) {
  return ((uint64_t)((SBO >> 4) | (SWZ << 30)) << 32) | (uint64_t)(lo + (byte_off >> 4));
}
__device__ __forceinline__ uint32_t pack2(float lo, float hi) { uint32_t r; asm("cvt.rn.bf16x2.f32 %0, %1, %2;" : "=r"(r) : "f"(hi), "f"(lo)); return r; }
__device__ __forceinline__ uint32_t pack2_relu(float lo, float hi) { uint32_t r; asm("cvt.rn.relu.bf16x2.f32 %0, %1, %2;" : "=r"(r) : "f"(hi), "f"(lo)); return r; }
__device__ __forceinline__ uint32_t sq2(uint32_t v) { uint32_t r; asm("mul.rn.bf16x2 %0, %1, %1;" : "=r"(r) : "r"(v)); return r; }
__device__ __forceinline__ float bf_lo(uint32_t v) { return __uint_as_float(v << 16); }
__device__ __forceinline__ float bf_hi(uint32_t v) { return __uint_as_float(v & 0xffff0000u); }
__device__ __forceinline__ float ex2(float x) { float r; asm("ex2.approx.ftz.f32 %0, %1;" : "=f"(r) : "f"(x)); return r; }
__device__ __forceinline__ float rcp(float x) { float r; asm("rcp.approx.ftz.f32 %0, %1;" : "=f"(r) : "f"(x)); return r; }
__device__ __forceinline__ float rsq(float x) { float r; asm("rsqrt.approx.ftz.f32 %0, %1;" : "=f"(r) : "f"(x)); return r; }
__device__ __forceinline__ void stsm4(uint32_t addr, uint32_t a, uint32_t b, uint32_t c, uint32_t d) {
  asm volatile("stmatrix.sync.aligned.m8n8.x4.shared.b16 [%0], {%1, %2, %3, %4};" :: "r"(addr), "r"(a), "r"(b), "r"(c), "r"(d) : "memory");
}
__device__ __forceinline__ void stsm2(uint32_t addr, uint32_t a, uint32_t b) {
  asm volatile("stmatrix.sync.aligned.m8n8.x2.shared.b16 [%0], {%1, %2};" :: "r"(addr), "r"(a), "r"(b) : "memory");
}
__device__ __forceinline__ void ldsm4(uint32_t addr, uint32_t (&r)[4]) {
  asm volatile("ldmatrix.sync.aligned.m8n8.x4.shared.b16 {%0, %1, %2, %3}, [%4];" : "=r"(r[0]), "=r"(r[1]), "=r"(r[2]), "=r"(r[3]) : "r"(addr) : "memory");
}
__device__ __forceinline__ float2 lds_f2(uint32_t a) { float2 v; asm volatile("ld.shared.v2.f32 {%0, %1}, [%2];" : "=f"(v.x), "=f"(v.y) : "r"(a)); return v; }
__device__ __forceinline__ float4 lds_f4(uint32_t a) { float4 v; asm volatile("ld.shared.v4.f32 {%0, %1, %2, %3}, [%4];" : "=f"(v.x), "=f"(v.y), "=f"(v.z), "=f"(v.w) : "r"(a)); return v; }
__device__ __forceinline__ uint4 lds_u4(uint32_t a) { uint4 v; asm volatile("ld.shared.v4.u32 {%0, %1, %2, %3}, [%4];" : "=r"(v.x), "=r"(v.y), "=r"(v.z), "=r"(v.w) : "r"(a)); return v; }
__device__ __forceinline__ void sts_f2(uint32_t a, float x, float y) { asm volatile("st.shared.v2.f32 [%0], {%1, %2};" :: "r"(a), "f"(x), "f"(y) : "memory"); }
__device__ __forceinline__ void sts_u4(uint32_t a, uint32_t x, uint32_t y, uint32_t z, uint32_t w) { asm volatile("st.shared.v4.u32 [%0], {%1, %2, %3, %4};" :: "r"(a), "r"(x), "r"(y), "r"(z), "r"(w) : "memory"); }
__device__ __forceinline__ void sts_u32(uint32_t a, uint32_t x) { asm volatile("st.shared.u32 [%0], %1;" :: "r"(a), "r"(x) : "memory"); }
__device__ __forceinline__ uint32_t lds_u32(uint32_t a) { uint32_t v; asm volatile("ld.shared.u32 %0, [%1];" : "=r"(v) : "r"(a) : "memory"); return v; }
__device__ __forceinline__ uint32_t ldg_u32(const void* p) { uint32_t v; asm volatile("ld.global.nc.u32 %0, [%1];" : "=r"(v) : "l"(p)); return v; }
__device__ __forceinline__ uint4 ldg_nc_u4(const void* p) { uint4 v; asm volatile("ld.global.nc.L1::no_allocate.v4.u32 {%0, %1, %2, %3}, [%4];" : "=r"(v.x), "=r"(v.y), "=r"(v.z), "=r"(v.w) : "l"(p)); return v; }
__device__ __forceinline__ void stg_u4(void* p, const uint4& v) { asm volatile("st.global.v4.u32 [%0], {%1, %2, %3, %4};" :: "l"(p), "r"(v.x), "r"(v.y), "r"(v.z), "r"(v.w) : "memory"); }
__device__ __forceinline__ void stg_u32(void* p, uint32_t v) { asm volatile("st.global.u32 [%0], %1;" :: "l"(p), "r"(v) : "memory"); }
__device__ __forceinline__ void stg_f2(void* p, float x, float y) { asm volatile("st.global.v2.f32 [%0], {%1, %2};" :: "l"(p), "f"(x), "f"(y) : "memory"); }
__device__ __forceinline__ void stg_zero16(void* p) { asm volatile("st.global.v4.u32 [%0], {%1, %1, %1, %1};" :: "l"(p), "r"(0) : "memory"); }
__device__ __forceinline__ float quad_max(float v) { v = fmaxf(v, __shfl_xor_sync(~0u, v, 1)); return fmaxf(v, __shfl_xor_sync(~0u, v, 2)); }
__device__ __forceinline__ float quad_sum(float v) { v += __shfl_xor_sync(~0u, v, 1); return v + __shfl_xor_sync(~0u, v, 2); }

__device__ __forceinline__ void wgmma_ss_n48_t1(float (&d)[24], uint64_t da, uint64_t db, int scale_d) {
  asm volatile("{\n.reg .pred p;\nsetp.ne.b32 p, %26, 0;\nwgmma.mma_async.sync.aligned.m64n48k16.f32.bf16.bf16 {%0, %1, %2, %3, %4, %5, %6, %7, %8, %9, %10, %11, %12, %13, %14, %15, %16, %17, %18, %19, %20, %21, %22, %23}, %24, %25, p, 1, 1, 0, 1;\n}"
    : "+f"(d[0]), "+f"(d[1]), "+f"(d[2]), "+f"(d[3]), "+f"(d[4]), "+f"(d[5]), "+f"(d[6]), "+f"(d[7]), "+f"(d[8]), "+f"(d[9]), "+f"(d[10]), "+f"(d[11]), "+f"(d[12]), "+f"(d[13]), "+f"(d[14]), "+f"(d[15]), "+f"(d[16]), "+f"(d[17]), "+f"(d[18]), "+f"(d[19]), "+f"(d[20]), "+f"(d[21]), "+f"(d[22]), "+f"(d[23])
    : "l"(da), "l"(db), "r"(scale_d));
}

__device__ __forceinline__ void wgmma_rs_n64_t0(float (&d)[32], uint32_t a0, uint32_t a1, uint32_t a2, uint32_t a3, uint64_t db, int scale_d) {
  asm volatile("{\n.reg .pred p;\nsetp.ne.b32 p, %37, 0;\nwgmma.mma_async.sync.aligned.m64n64k16.f32.bf16.bf16 {%0, %1, %2, %3, %4, %5, %6, %7, %8, %9, %10, %11, %12, %13, %14, %15, %16, %17, %18, %19, %20, %21, %22, %23, %24, %25, %26, %27, %28, %29, %30, %31}, {%32, %33, %34, %35}, %36, p, 1, 1, 0;\n}"
    : "+f"(d[0]), "+f"(d[1]), "+f"(d[2]), "+f"(d[3]), "+f"(d[4]), "+f"(d[5]), "+f"(d[6]), "+f"(d[7]), "+f"(d[8]), "+f"(d[9]), "+f"(d[10]), "+f"(d[11]), "+f"(d[12]), "+f"(d[13]), "+f"(d[14]), "+f"(d[15]), "+f"(d[16]), "+f"(d[17]), "+f"(d[18]), "+f"(d[19]), "+f"(d[20]), "+f"(d[21]), "+f"(d[22]), "+f"(d[23]), "+f"(d[24]), "+f"(d[25]), "+f"(d[26]), "+f"(d[27]), "+f"(d[28]), "+f"(d[29]), "+f"(d[30]), "+f"(d[31])
    : "r"(a0), "r"(a1), "r"(a2), "r"(a3), "l"(db), "r"(scale_d));
}

__device__ __forceinline__ void wgmma_rs_n24_t1(float (&d)[12], uint32_t a0, uint32_t a1, uint32_t a2, uint32_t a3, uint64_t db, int scale_d) {
  asm volatile("{\n.reg .pred p;\nsetp.ne.b32 p, %17, 0;\nwgmma.mma_async.sync.aligned.m64n24k16.f32.bf16.bf16 {%0, %1, %2, %3, %4, %5, %6, %7, %8, %9, %10, %11}, {%12, %13, %14, %15}, %16, p, 1, 1, 1;\n}"
    : "+f"(d[0]), "+f"(d[1]), "+f"(d[2]), "+f"(d[3]), "+f"(d[4]), "+f"(d[5]), "+f"(d[6]), "+f"(d[7]), "+f"(d[8]), "+f"(d[9]), "+f"(d[10]), "+f"(d[11])
    : "r"(a0), "r"(a1), "r"(a2), "r"(a3), "l"(db), "r"(scale_d));
}

__device__ __forceinline__ void wgmma_ss_n80_t1(float (&d)[40], uint64_t da, uint64_t db, int scale_d) {
  asm volatile("{\n.reg .pred p;\nsetp.ne.b32 p, %42, 0;\nwgmma.mma_async.sync.aligned.m64n80k16.f32.bf16.bf16 {%0, %1, %2, %3, %4, %5, %6, %7, %8, %9, %10, %11, %12, %13, %14, %15, %16, %17, %18, %19, %20, %21, %22, %23, %24, %25, %26, %27, %28, %29, %30, %31, %32, %33, %34, %35, %36, %37, %38, %39}, %40, %41, p, 1, 1, 0, 1;\n}"
    : "+f"(d[0]), "+f"(d[1]), "+f"(d[2]), "+f"(d[3]), "+f"(d[4]), "+f"(d[5]), "+f"(d[6]), "+f"(d[7]), "+f"(d[8]), "+f"(d[9]), "+f"(d[10]), "+f"(d[11]), "+f"(d[12]), "+f"(d[13]), "+f"(d[14]), "+f"(d[15]), "+f"(d[16]), "+f"(d[17]), "+f"(d[18]), "+f"(d[19]), "+f"(d[20]), "+f"(d[21]), "+f"(d[22]), "+f"(d[23]), "+f"(d[24]), "+f"(d[25]), "+f"(d[26]), "+f"(d[27]), "+f"(d[28]), "+f"(d[29]), "+f"(d[30]), "+f"(d[31]), "+f"(d[32]), "+f"(d[33]), "+f"(d[34]), "+f"(d[35]), "+f"(d[36]), "+f"(d[37]), "+f"(d[38]), "+f"(d[39])
    : "l"(da), "l"(db), "r"(scale_d));
}

__device__ __forceinline__ void wgmma_ss_n192_t1(float (&d)[96], uint64_t da, uint64_t db, int scale_d) {
  asm volatile("{\n.reg .pred p;\nsetp.ne.b32 p, %98, 0;\nwgmma.mma_async.sync.aligned.m64n192k16.f32.bf16.bf16 {%0, %1, %2, %3, %4, %5, %6, %7, %8, %9, %10, %11, %12, %13, %14, %15, %16, %17, %18, %19, %20, %21, %22, %23, %24, %25, %26, %27, %28, %29, %30, %31, %32, %33, %34, %35, %36, %37, %38, %39, %40, %41, %42, %43, %44, %45, %46, %47, %48, %49, %50, %51, %52, %53, %54, %55, %56, %57, %58, %59, %60, %61, %62, %63, %64, %65, %66, %67, %68, %69, %70, %71, %72, %73, %74, %75, %76, %77, %78, %79, %80, %81, %82, %83, %84, %85, %86, %87, %88, %89, %90, %91, %92, %93, %94, %95}, %96, %97, p, 1, 1, 0, 1;\n}"
    : "+f"(d[0]), "+f"(d[1]), "+f"(d[2]), "+f"(d[3]), "+f"(d[4]), "+f"(d[5]), "+f"(d[6]), "+f"(d[7]), "+f"(d[8]), "+f"(d[9]), "+f"(d[10]), "+f"(d[11]), "+f"(d[12]), "+f"(d[13]), "+f"(d[14]), "+f"(d[15]), "+f"(d[16]), "+f"(d[17]), "+f"(d[18]), "+f"(d[19]), "+f"(d[20]), "+f"(d[21]), "+f"(d[22]), "+f"(d[23]), "+f"(d[24]), "+f"(d[25]), "+f"(d[26]), "+f"(d[27]), "+f"(d[28]), "+f"(d[29]), "+f"(d[30]), "+f"(d[31]), "+f"(d[32]), "+f"(d[33]), "+f"(d[34]), "+f"(d[35]), "+f"(d[36]), "+f"(d[37]), "+f"(d[38]), "+f"(d[39]), "+f"(d[40]), "+f"(d[41]), "+f"(d[42]), "+f"(d[43]), "+f"(d[44]), "+f"(d[45]), "+f"(d[46]), "+f"(d[47]), "+f"(d[48]), "+f"(d[49]), "+f"(d[50]), "+f"(d[51]), "+f"(d[52]), "+f"(d[53]), "+f"(d[54]), "+f"(d[55]), "+f"(d[56]), "+f"(d[57]), "+f"(d[58]), "+f"(d[59]), "+f"(d[60]), "+f"(d[61]), "+f"(d[62]), "+f"(d[63]), "+f"(d[64]), "+f"(d[65]), "+f"(d[66]), "+f"(d[67]), "+f"(d[68]), "+f"(d[69]), "+f"(d[70]), "+f"(d[71]), "+f"(d[72]), "+f"(d[73]), "+f"(d[74]), "+f"(d[75]), "+f"(d[76]), "+f"(d[77]), "+f"(d[78]), "+f"(d[79]), "+f"(d[80]), "+f"(d[81]), "+f"(d[82]), "+f"(d[83]), "+f"(d[84]), "+f"(d[85]), "+f"(d[86]), "+f"(d[87]), "+f"(d[88]), "+f"(d[89]), "+f"(d[90]), "+f"(d[91]), "+f"(d[92]), "+f"(d[93]), "+f"(d[94]), "+f"(d[95])
    : "l"(da), "l"(db), "r"(scale_d));
}

__device__ __forceinline__ void wgmma_rs_n64_t1(float (&d)[32], uint32_t a0, uint32_t a1, uint32_t a2, uint32_t a3, uint64_t db, int scale_d) {
  asm volatile("{\n.reg .pred p;\nsetp.ne.b32 p, %37, 0;\nwgmma.mma_async.sync.aligned.m64n64k16.f32.bf16.bf16 {%0, %1, %2, %3, %4, %5, %6, %7, %8, %9, %10, %11, %12, %13, %14, %15, %16, %17, %18, %19, %20, %21, %22, %23, %24, %25, %26, %27, %28, %29, %30, %31}, {%32, %33, %34, %35}, %36, p, 1, 1, 1;\n}"
    : "+f"(d[0]), "+f"(d[1]), "+f"(d[2]), "+f"(d[3]), "+f"(d[4]), "+f"(d[5]), "+f"(d[6]), "+f"(d[7]), "+f"(d[8]), "+f"(d[9]), "+f"(d[10]), "+f"(d[11]), "+f"(d[12]), "+f"(d[13]), "+f"(d[14]), "+f"(d[15]), "+f"(d[16]), "+f"(d[17]), "+f"(d[18]), "+f"(d[19]), "+f"(d[20]), "+f"(d[21]), "+f"(d[22]), "+f"(d[23]), "+f"(d[24]), "+f"(d[25]), "+f"(d[26]), "+f"(d[27]), "+f"(d[28]), "+f"(d[29]), "+f"(d[30]), "+f"(d[31])
    : "r"(a0), "r"(a1), "r"(a2), "r"(a3), "l"(db), "r"(scale_d));
}

struct Params {
  const __nv_bfloat16* x; const __nv_bfloat16* wqkv; const __nv_bfloat16* wo; const __nv_bfloat16* w1;
  const __nv_bfloat16* b1; const __nv_bfloat16* w2; const __nv_bfloat16* b2; __nv_bfloat16* out; Scratch* scr;
  uint32_t sched[3][2][12];
};
enum : uint32_t { S_OWN = 1u << 19, S_FAR = 2u << 19, S_MASK = 3u << 19  , S_WAIT = 1u << 21  ,
                  S_OSW = 1u << 24  , S_END = 1u << 27, S_CUR = 1u << 29   };
constexpr float SM_SCALE = 0.22360679774997896f * 1.4426950408889634f;

__global__ void __launch_bounds__(384, 1)
fused_block_kernel(const __grid_constant__ CUtensorMap mX, const __grid_constant__ CUtensorMap mWq, const __grid_constant__ CUtensorMap mWr,
                   const __grid_constant__ CUtensorMap mW1,
                   const __grid_constant__ CUtensorMap mW1r, const __grid_constant__ CUtensorMap mW2, const __grid_constant__ CUtensorMap mOut, const __grid_constant__ CUtensorMap mXr,
                   const __grid_constant__ Params p) {
  extern __shared__ __align__(1024) uint8_t smem_raw[];
  const uint32_t sb = smem_u32(smem_raw);
  const int tid = threadIdx.x, lane = tid & 31;
  const int warp = __shfl_sync(~0u, tid >> 5, 0);
  const int cta = blockIdx.x, rank = cta & 1, pair = cta >> 1;
  const int hq = pair & 7, rbA = (pair >> 3) * 2 + rank;
  const int rbC = pair >> 2, jj = pair & 3, j = jj * 2 + rank;
  const int colM = 320 * rank + 64 * jj, colR = 320 * rank + 256 + 16 * jj;
  if ((sb & 0x3FFFF) != SB0) __trap();
  const uint32_t bars = sb + BARS;
  auto bar = [&](int i) { return bars + i * 8; };
  unsigned nspin = 0;

  if (warp == 8) {
    if (elect_one()) {
      prefetch_map(&mX); prefetch_map(&mWq); prefetch_map(&mWr);
      #pragma unroll
      for (int i = 0; i < 4; i++) { mbar_init(bar(B_AFULL + i), 1); mbar_init(bar(B_AEMPTY + i), 16); }
      mbar_init(bar(B_A0), 1);
      asm volatile("fence.mbarrier_init.release.cluster;" ::: "memory");
      fence_async();
      mbar_expect_tx(bar(B_A0), 16384 + 15360);
      mbar_expect_tx(bar(B_AFULL), 15360);
      tma_2d(sb, &mX, 0, rbA * 128, bar(B_A0));
      #pragma unroll 1
      for (int h = 0; h < 2; h++) {
        tma_3d(sb + 16384 + h * 15360, &mWq, 80 * hq, 32 * h, 0, bar(h ? B_AFULL : B_A0));
        tma_3d(sb + 16384 + h * 15360 + 12288, &mWr, 80 * hq + 64, 32 * h, 0, bar(h ? B_AFULL : B_A0));
      }
      #pragma unroll 1
      for (int it = 1; it < PRE_N; it++) { mbar_expect_tx(bar(B_AFULL + it), A_STAGE); tma_2d(sb + it * A_STAGE, &mX, it * 64, rbA * 128, bar(B_AFULL + it)); }
    }
    __syncwarp();
  }
  asm volatile("barrier.cluster.arrive.relaxed.aligned;" ::: "memory");
  if (warp != 8 && elect_one()) {
    #pragma unroll 1
    for (int i = 8 + (warp < 8 ? warp : warp - 1); i < B_COUNT; i += 11) mbar_init(bar(i), bar_count(i));
    if (warp == 11) {
      mbar_init(bar(B_PF), 8);
      #pragma unroll 1
      for (int i = 0; i < 10; i++) mbar_init(bar(B_ST + i), 4);
      mbar_init(bar(B_P1D), 2); mbar_init(bar(B_OW), 8); mbar_init(bar(B_OW + 1), 8);
      #pragma unroll 1
      for (int i = 0; i < 4; i++) mbar_init(bar(B_CFULL + i), 1);
    }
    asm volatile("fence.mbarrier_init.release.cluster;" ::: "memory");
  }
  __syncwarp();
  cluster_wait();
  auto w_loads = [&](int it) {
    const uint32_t full = bar(B_AFULL + (it & 3)), dst = sb + (it & 3) * A_STAGE + 16384 + rank * 15360;
    tma_3d_mc(dst, &mWq, 80 * hq, it * 64 + 32 * rank, 0, full);
    tma_3d_mc(dst + 12288, &mWr, 80 * hq + 64, it * 64 + 32 * rank, 0, full);
  };
  if (warp == 8 && elect_one()) {
    #pragma unroll 1
    for (int it = 1; it < PRE_N; it++) w_loads(it);
  }
  __syncthreads();

  if (warp >= 8) {
    asm volatile("setmaxnreg.dec.sync.aligned.u32 56;");
    auto add_partials = [&](int w, unsigned tag) {
      if (lane < 8) wait_flag(&p.scr->flags[FL_I + rbC * 8 + lane], tag, nspin);
      __syncwarp();
      cluster_arrive();
      if (elect_one()) {
        fence_async_global();
        #pragma unroll 1
        for (int k = 0; k < 5; k++) {
          mbar_wait(bar(B_ST + 2 * k + w), 0, nspin);
          const uint32_t off = k < 3 ? (rank ^ 1) * 49152 + k * 16384 : eb_off(k - 3);
          tma_red_add(&mOut, sb + off + w * 8192, 320 * rank + (k == 0 ? 64 * jj : k == 1 ? 256 : 64 * ((jj + k - 1) & 3)), rbC * 128 + w * 64);
          bulk_commit();
        }
        bulk_wait_read0();
      }
    };
    unsigned tag = 0;
    if (warp > 8) tag = ld_relaxed(&p.scr->flags[FL_EPOCH + cta]);
    auto publish_kv = [&](int P) {
      mbar_wait(bar(B_KVW + 1 - P), 0, nspin);
      bulk_st(&p.scr->kv[(rbA * 8 + hq) * (KV_BLK / 16) + P * (KV_HALF / 16)], sb + kv_off(P, 0), KV_HALF);
      bulk_commit();
      bulk_wait0();
      fence_async_global();
      fence_acq();
      #pragma unroll
      for (int d = 1; d < 3; d++)
        if (rbA + d < 16) st_relaxed(&p.scr->flags[FL_CTA + (((((rbA + d) >> 1) * 8 + hq) << 1) | ((rbA + d) & 1)) * 32 + FW_KV + 2 * (1 - P) + d - 1], tag);
    };
    const auto publish_h = [&]() {
      fence_acq();
      #pragma unroll
      for (int c = 2; c < 8; c++) st_relaxed(&p.scr->flags[FL_CTA + (rbC * 8 + (j ^ c)) * 32 + FW_H + j], tag);
    };
    float acc[8];
    #pragma unroll
    for (int i = 0; i < 8; i++) acc[i] = 0.f;
    auto cs_add = [&](const __nv_bfloat16* src, int ld, uint32_t sl, int n) {
      #pragma unroll 1
      for (int i = 0; i < n; i++) { cp_async16(sl + i * 512, src); src += 16 * ld; }
      cp_async_wait_all();
      #pragma unroll 1
      for (int i = 0; i < n; i += 8) {
        uint4 v[8];
        #pragma unroll
        for (int u = 0; u < 8; u++) v[u] = lds_u4(sl + (i + u) * 512);
        #pragma unroll
        for (int u = 0; u < 8; u++) {
          acc[0] += bf_lo(v[u].x); acc[1] += bf_hi(v[u].x); acc[2] += bf_lo(v[u].y); acc[3] += bf_hi(v[u].y);
          acc[4] += bf_lo(v[u].z); acc[5] += bf_hi(v[u].z); acc[6] += bf_lo(v[u].w); acc[7] += bf_hi(v[u].w);
        }
      }
    };
    auto cs_reduce = [&]() {
      #pragma unroll
      for (int o = 0; o < 3; o++) {
        const bool up = (lane >> (o + 1)) & 1;
        #pragma unroll
        for (int i = 0; i < (4 >> o); i++) {
          const float keep = up ? acc[2 * i + 1] : acc[2 * i], give = up ? acc[2 * i] : acc[2 * i + 1];
          acc[i] = keep + __shfl_xor_sync(~0u, give, 2 << o);
        }
      }
      return acc[0] + __shfl_xor_sync(~0u, acc[0], 16);
    };
    float cs0 = 0.f;
    if (warp > 8) {
      if (cta < 120) {
        mbar_wait(bar(B_AFULL), 0, nspin);
        const int i0 = (warp - 9) * 16;
        cs_add(p.wqkv + (size_t)((lane >> 1) + 16 * i0) * (3 * DM) + cta * 16 + (lane & 1) * 8, 3 * DM, sb + CS_STG0 + lane * 16 + i0 * 512, warp < 11 ? 16 : 8);
        cs0 = cs_reduce();
        if (warp < 11 && lane < 16) sts_u32(sb + S_PART + (warp - 9) * 64 + lane * 4, __float_as_uint(cs0));
      }
      named_sync(4, 96);
      asm volatile("add.u32 %0, %0, 1;" : "+r"(tag));
    }
    if (warp == 11) {
      #pragma unroll 1
      for (int job = 0; job < 2; job++) {
        if (job && elect_one()) {
          publish_kv(0);
          mbar_arrive(bar(B_KVST));
        }
        __syncwarp();
        if (cta < (job ? 96 : 120)) {
          float v;
          if (job) {
            #pragma unroll
            for (int i = 0; i < 8; i++) acc[i] = 0.f;
            #pragma unroll 1
            for (int r0 = 0; r0 < 40; r0 += 16)
              cs_add(p.w1 + (size_t)((lane >> 1) + 16 * r0) * FF + cta * 16 + (lane & 1) * 8, FF, sb + CS_STG1 + lane * 16, r0 < 32 ? 16 : 8);
            v = cs_reduce();
          } else {
            v = cs0 + __uint_as_float(lds_u32(sb + S_PART + (lane & 15) * 4)) + __uint_as_float(lds_u32(sb + S_PART + 64 + (lane & 15) * 4));
          }
          if (lane < 16) st_relaxed64(&p.scr->cs[(job ? 3 * DM : 0) + cta * 16 + (lane & 1) * 8 + (lane >> 1)], __float_as_uint(v), tag);
        }
        __syncwarp();
        if (elect_one()) {
          mbar_arrive(bar(job ? B_AUX2 : B_AUXDONE));
          if (job == 0) {
            st_relaxed(&p.scr->flags[FL_EPOCH + cta], tag);
          }
        }
        __syncwarp();
        const int n = job ? 96 : 120;
        const uint32_t dst = sb + (job ? S_CS2 : S_CS1);
        const uint4* csrc = reinterpret_cast<const uint4*>(job ? &p.scr->cs[3 * DM + 192 * j] : &p.scr->cs[80 * hq]);
        bool ok;
        do {
          #pragma unroll 1
          for (int c = lane; c < n; c += 32) cp_async16(dst + c * 16, csrc + c + (job ? 0 : (c >= 40 ? 280 : 0) + (c >= 80 ? 280 : 0)));
          cp_async_wait_all();
          ok = true;
          #pragma unroll 1
          for (int c = lane; c < n; c += 32) { const uint4 v = lds_u4(dst + c * 16); ok = ok && v.y == tag && v.w == tag; }
          ok = __all_sync(~0u, ok);
          if (SLOW_NS && job && !ok) __nanosleep(SLOW_NS);
        } while (!ok && ++nspin < SPIN_LIMIT);
        if (job) {
          #pragma unroll 1
          for (int c = lane; c < 96; c += 32) {
            const uint32_t bb = ldg_u32(p.b1 + 192 * j + 2 * c);
            sts_u32(dst + c * 16 + 4, bb << 16); sts_u32(dst + c * 16 + 12, bb & 0xffff0000u);
          }
        }
        __syncwarp();
        if (lane == 0) mbar_arrive(bar(job ? B_CS2 : B_STAT));
        if (job == 0 && lane == 0) {
          prefetch_l2(reinterpret_cast<const uint8_t*>(p.wo) + cta * 6400, 6400);
          prefetch_l2(reinterpret_cast<const uint8_t*>(p.w1) + cta * 15360, 15360);
          prefetch_l2(reinterpret_cast<const uint8_t*>(p.w2) + cta * 15360, 15360);
        }
      }
      __syncwarp();
      cluster_arrive();
    } else if (warp == 10) {
      if (elect_one()) publish_kv(1);
      __syncwarp();
      {
        const int tq = rbC >> 1, hp = rbC & 1;
        const __nv_bfloat16* src = p.wo + (size_t)(80 * (2 * (tq & 3) + hp) + (tq < 4 ? 40 : 0)) * DM;
        uint8_t* dst = reinterpret_cast<uint8_t*>(p.scr->wo) + (j * 8 + tq) * WO_BYTES + hp * 1280;
        #pragma unroll 1
        for (int b = 0; b < 3; b++) {
          uint4 v[5];
          #pragma unroll
          for (int i = 0; i < 5; i++) {
            const int r = b < 2 ? 20 * b + 4 * i + (lane >> 3) : 16 * i + (lane >> 1);
            if (r < 40) v[i] = ldg_nc_u4(src + r * DM + (b < 2 ? colM + (lane & 7) * 8 : colR + (lane & 1) * 8));
          }
          #pragma unroll
          for (int i = 0; i < 5; i++) {
            const int r = b < 2 ? 20 * b + 4 * i + (lane >> 3) : 16 * i + (lane >> 1);
            if (r < 40) stg_u4(dst + (b < 2 ? (lane & 7) >> 1 : 4) * 2560 + r * 32 + (((lane ^ (r >> 2)) & 1) << 4), v[i]);
          }
        }
        uint4* o = reinterpret_cast<uint4*>(p.out + (size_t)(rbC * 128 + j * 16) * DM) + lane;
        #pragma unroll 4
        for (int i = 0; i < 40; i++) stg_zero16(o + i * 32);
        __syncwarp();
        if (lane == 0) st_release(&p.scr->flags[FL_I + rbC * 8 + j], tag);
      }
      if (elect_one()) {
        #pragma unroll 1
        for (int P = 1; P >= 0; P--) {
          mbar_wait(bar(B_OW + P), 0, nspin);
          if (P) { mbar_arrive_cluster(bar(B_P1D), 0); mbar_arrive_cluster(bar(B_P1D), 1); }
          fence_acq();
          #pragma unroll
          for (int c = 0; c < 4; c++) st_relaxed(&p.scr->flags[FL_CTA + (rbA * 8 + 2 * c + (hq & 1)) * 32 + FW_O + 8 * P + hq], tag);
          if (!P) {
            mbar_wait(bar(B_KVST), 0, nspin);
            #pragma unroll 1
            for (int q = 0; q < 4; q++) {
              mbar_expect_tx(bar(B_WOL + q), WO_BYTES);
              bulk_ld(sb + WOL_OFF + q * WO_BYTES, reinterpret_cast<const uint8_t*>(p.scr->wo) + (j * 8 + 4 + q) * WO_BYTES, WO_BYTES, bar(B_WOL + q));
            }
          }
        }
        mbar_wait(bar(B_HW), 0, nspin);
        mbar_arrive(bar(B_DAFULL + 0));
        publish_h();
        mbar_wait(bar(B_CDONE), 0, nspin);
        bulk_dsmem(mapa(sb + HT_BYTES, rank ^ 1), sb, HT_BYTES, mapa(bar(B_DAFULL + 1), rank ^ 1));
        mbar_wait(bar(B_DDONE), 0, nspin);
        #pragma unroll 1
        for (int i = 0; i < 3; i++) {
          mbar_wait(bar(i == 2 ? B_FW : B_KVW + i), i == 2 ? 0 : 1, nspin);
          const uint32_t off = rank * 49152 + i * 16384;
          bulk_dsmem(mapa(sb + off, rank ^ 1), sb + off, 16384, mapa(bar(B_FFULL + i), rank ^ 1));
        }
      }
      __syncwarp();
      add_partials(0, tag);
    } else if (warp == 9) {
      if (elect_one()) {
        mbar_wait(bar(B_KVW), 0, nspin);
        #pragma unroll 1
        for (int c = 0; c < 4; c++) {
          const int d = 1 + (c & 1), blk = (rbA - d) * 8 + hq;
          if (rbA >= d) {
            wait_flag<KV_NS>(&p.scr->flags[FL_CTA + cta * 32 + FW_KV + c], tag, nspin);
            fence_async_global();
            mbar_expect_tx(bar(B_KVFULL + c), KV_HALF);
            bulk_ld(sb + kv_off(c < 2, d), reinterpret_cast<const uint8_t*>(p.scr->kv) + blk * KV_BLK + (c < 2 ? KV_HALF : 0), KV_HALF, bar(B_KVFULL + c));
          }
        }
        mbar_expect_tx(bar(B_XR), 20480);
        tma_2d(sb + XR_OFF, &mX, colM, rbC * 128, bar(B_XR));
        tma_2d(sb + XR1_OFF, &mXr, colR, rbC * 128, bar(B_XR));
      }
      const uint8_t* wimg = reinterpret_cast<const uint8_t*>(p.scr->wo) + j * 8 * WO_BYTES;
      if (lane < 16) wait_flag<SLOW_NS>(&p.scr->flags[FL_I + lane * 8 + j], tag, nspin);
      __syncwarp();
      if (elect_one()) {
        fence_async_global();
        mbar_wait(bar(B_AUXDONE), 0, nspin);
        mbar_expect_tx(bar(B_WOFULL), 4 * WO_BYTES);
        bulk_ld(sb + WOE_OFF, wimg, 4 * WO_BYTES, bar(B_WOFULL));
      }
      #pragma unroll 1
      for (int job = 0; job < 3; job++) {
        const bool hjob = job == 2;
        const uint32_t half = hjob ? HT_BYTES / 2 : OT_HALF;
        if (elect_one()) {
          if (job == 0) mbar_wait(bar(B_P1D), 0, nspin);
          else if (job == 2) {
            mbar_expect_tx(bar(B_DAFULL + 1), HT_BYTES);
            #pragma unroll 1
            for (int i = 0; i < 3; i++) mbar_expect_tx(bar(B_FFULL + i), 16384);
            mbar_wait(bar(B_CDONE), 0, nspin);
          }
        }
        __syncwarp();
        const auto hkt = [&](int n) { return ((jj + (n >> 1)) & 3) * 2 + (n & 1); };
        const unsigned* fl = &p.scr->flags[FL_CTA + cta * 32 + (hjob ? FW_H + hkt(lane & 7) : FW_O + 8 * (1 - job) + (lane & 3) * 2 + rank)];
        const uint8_t* src = hjob ? reinterpret_cast<const uint8_t*>(p.scr->h) + rbC * 8 * HT_BYTES + rank * half
                                  : reinterpret_cast<const uint8_t*>(p.scr->o) + (rbC * 8 + rank) * OT_BYTES + (1 - job) * OT_HALF;
        int next = hjob ? 2 : 0;
        const int end = hjob ? 8 : 4;
        #pragma unroll 1
        for (unsigned spin = 0; next < end && spin < SPIN_LIMIT; spin++) {
          const unsigned ready = __ballot_sync(~0u, (int)(ld_acquire(fl) - tag) >= 0) & ((1u << end) - 1);
          const int stop = next + __ffs(~(ready >> next)) - 1;
          if (stop > next && elect_one()) {
            fence_async_global();
            #pragma unroll 1
            for (int n = next; n < stop; n++) {
              const int s = n & 3;
              if (hjob ? n >= 4 : job) mbar_wait(bar((hjob ? B_DAEMPTY : B_CEMPTY) + s), 0, nspin);
              if (hjob && n == 4) mbar_wait(bar(B_P1D), 1, nspin);
              const uint32_t full = bar((hjob ? B_DAFULL : B_CFULL) + s);
              mbar_expect_tx(full, 2 * half);
              bulk_ld_mc(sb + (hjob ? s * HT_BYTES : ot_off(s)) + rank * half, src + (hjob ? hkt(n) * HT_BYTES : n * 2 * OT_BYTES), half, full);
            }
          }
          __syncwarp();
          next = stop;
        }
        if (job == 1 && lane == 0) mbar_arrive(bar(B_OST));
      }
      add_partials(1, tag);
    } else {
      if (elect_one()) {
        #pragma unroll 1
        for (int it = PRE_N; it < 10; it++) {
          const int s = it & 3;
          if (it == PRE_N) mbar_wait(bar(B_A0), 0, nspin);
          if (it >= 4) mbar_wait(bar(B_AEMPTY + s), ((it >> 2) - 1) & 1, nspin);
          mbar_expect_tx(bar(B_AFULL + s), A_STAGE);
          tma_2d(sb + s * A_STAGE, &mX, it * 64, rbA * 128, bar(B_AFULL + s));
          w_loads(it);
        }
        prefetch_map(&mXr); prefetch_map(&mW1); prefetch_map(&mW1r); prefetch_map(&mW2);
        mbar_wait(bar(B_AUX2), 0, nspin);
        #pragma unroll 1
        for (int t = 0; t < 8; t++) {
          const int s = t & 3;
          if (t == 0) {
            mbar_wait(bar(B_CEMPTY + 3), 0, nspin);
            mbar_wait(bar(B_OST), 0, nspin);
          }
          if (t == 2) { mbar_wait(bar(B_CDONE), 0, nspin); }
          if (t >= 4) mbar_wait(bar(B_DBEMPTY + s), 0, nspin);
          const int kt = t < 2 ? (j ^ t) : (((jj + (t >> 1)) & 3) * 2 + (t & 1));
          const uint32_t full = bar(B_DBFULL + s), dst = sb + db_off(s);
          mbar_expect_tx(full, 30720);
          #pragma unroll 1
          for (int c = 0; c < 3; c++) {
            tma_2d(dst + c * 10240, &mW1, 192 * j + 64 * c, 320 * (kt & 1) + 64 * (kt >> 1), full);
            tma_2d(dst + c * 10240 + 8192, &mW1r, 192 * j + 64 * c, 320 * (kt & 1) + 256 + 16 * (kt >> 1), full);
          }
        }
        #pragma unroll 1
        for (int i = 0; i < 10; i++) {
          const int s = i < 5 ? i : i - 5;
          mbar_wait(bar(i < 5 ? B_DBEMPTY + (i < 2 ? 1 : i < 4 ? i : 3) : B_EBEMPTY + s), i < 5 ? 1 : 0, nspin);
          const uint32_t full = bar(B_EBFULL + s), dst = sb + eb_off(s);
          mbar_expect_tx(full, EB_SLOT);
          const int k = i < 4 ? i & 1 : i >> 1, h = i < 4 ? i >> 1 : i & 1;
          #pragma unroll 1
          for (int c = 0; c < 3; c++) tma_2d(dst + c * 8192, &mW2, 320 * rank + (k == 0 ? 64 * jj : k == 1 ? 256 : 64 * ((jj + k - 1) & 3)), 384 * jj + 192 * (rank ^ h) + 64 * c, full);
        }
        prefetch_map(&mOut);
      }
      __syncwarp();
      cluster_arrive();
    }
  } else {
    asm volatile("setmaxnreg.inc.sync.aligned.u32 224;");
    const int wg = warp >> 2, g = lane >> 2, c4 = lane & 3;
    auto release_pair = [&](int b) { if ((tid & 127) < 2) mbar_arrive_cluster(bar(b), tid & 1); };
    if (tid < 64) { sts_u4(sb + S_KC + tid * 16, 0x3F803F80u, 0x3F80u, tid < 16 ? 0x3F80u : tid < 32 ? 0x3F800000u : 0u, tid >= 48 ? 0x3F800000u : tid >= 32 ? 0x3F80u : 0u); fence_async(); }
    const int rbw = warp;
    uint32_t qf[10][2];
    {
      float acc[96], acr[24];
      float sx0 = 0.f, sq0 = 0.f, sx1 = 0.f, sq1 = 0.f;
      const uint32_t arow = rbw * 16 + (lane & 7) + ((lane >> 3) & 1) * 8;
      const uint32_t aoff = sb + arow * 128 + (((lane >> 4) ^ (arow & 7)) << 4);
      const uint32_t alo = desc_lo(wg * 8192, 16), lo192 = desc_lo(16384, 4096), lo48 = desc_lo(16384 + 12288, 1024);
      #pragma unroll 1
      for (int it = 0; it < 10; it++) {
        const int s = it & 3;
        mbar_wait(bar(it == 0 ? B_A0 : B_AFULL + s), (it >> 2) & 1, nspin);
        const uint32_t so = s * A_STAGE;
        #pragma unroll
        for (int hh = 0; hh < 2; hh++) {
          if (hh == 1 && it == 0) mbar_wait(bar(B_AFULL), 0, nspin);
          wg_fence();
          #pragma unroll
          for (int kk = 2 * hh; kk < 2 * hh + 2; kk++) {
            const int sc = (it > 0 || kk > 0) ? 1 : 0;
            const uint64_t da = desc<1024, 1>(alo + (so >> 4), kk * 32);
            wgmma_ss_n192_t1(acc, da, desc<1024, 1>(lo192 + (so >> 4), hh * 15360 + (kk & 1) * 2048), sc);
            wgmma_ss_n48_t1(acr, da, desc<256, 3>(lo48 + (so >> 4), hh * 15360 + (kk & 1) * 512), sc);
          }
          wg_commit();
          #pragma unroll
          for (int kk = 2 * hh; kk < 2 * hh + 2; kk++) {
            uint32_t af[4];
            ldsm4((aoff ^ (kk * 32)) + so, af);
            #pragma unroll
            for (int u = 0; u < 4; u++) {
              const float lo = bf_lo(af[u]), hi = bf_hi(af[u]);
              if (u & 1) { sx1 += lo + hi; sq1 = fmaf(lo, lo, fmaf(hi, hi, sq1)); }
              else { sx0 += lo + hi; sq0 = fmaf(lo, lo, fmaf(hi, hi, sq0)); }
            }
          }
          wg_wait<1>();
          if (hh == 0 && it > 0 && lane < 2) mbar_arrive_cluster(bar(B_AEMPTY + ((it - 1) & 3)), lane);
        }
      }
      wg_wait<0>();
      reg_fence(acc); reg_fence(acr);
      const float mu0 = quad_sum(sx0) * (1.f / DM), mu1 = quad_sum(sx1) * (1.f / DM);
      const float rs0 = rsq(fmaxf(quad_sum(sq0) * (1.f / DM) - mu0 * mu0, 0.f) + 1e-5f), rs1 = rsq(fmaxf(quad_sum(sq1) * (1.f / DM) - mu1 * mu1, 0.f) + 1e-5f);
      const float mr0 = -mu0 * rs0, mr1 = -mu1 * rs1;
      mbar_wait(bar(B_STAT), 0, nspin);
      const uint32_t csa = sb + S_CS1 + c4 * 16;
      auto cs_ld = [&](int n) {
        const int P = n < 10 ? 1 : 0, m = n - (n < 10 ? 0 : 10), sec = n >= 20 ? 0 : m < 5 ? 1 : 2, t = n >= 20 ? n - 20 : 5 * P + (m < 5 ? m : m - 5);
        return lds_f4(csa + (80 * sec + 8 * t) * 8);
      };
      float4 csn[2] = {cs_ld(0), cs_ld(1)};
      auto norm2 = [&](int n, uint32_t& lo, uint32_t& hi) {
        const int P = n < 10 ? 1 : 0, m = n - (n < 10 ? 0 : 10), sec = n >= 20 ? 0 : m < 5 ? 1 : 2, t = n >= 20 ? n - 20 : 5 * P + (m < 5 ? m : m - 5);
        const float4 cs = csn[n & 1];
        if (n + 2 < 30) csn[n & 1] = cs_ld(n + 2);
        const float* a = t < 8 ? &acc[4 * (8 * sec + t)] : &acr[4 * (2 * sec + t - 8)];
        const float r0 = sec ? rs0 : rs0 * SM_SCALE, r1 = sec ? rs1 : rs1 * SM_SCALE, n0 = sec ? mr0 : mr0 * SM_SCALE, n1 = sec ? mr1 : mr1 * SM_SCALE;
        lo = pack2(fmaf(a[0], r0, cs.x * n0), fmaf(a[1], r0, cs.z * n0));
        hi = pack2(fmaf(a[2], r1, cs.x * n1), fmaf(a[3], r1, cs.z * n1));
      };
      mbar_wait(bar(B_AEMPTY + 2), 1, nspin);
      const uint32_t stA = sb + kv_off(0, 0) + (uint32_t)(rbw * 16 + ((lane >> 3) & 1) * 8 + (lane & 7)) * 16 + (uint32_t)(lane >> 4) * 2048;
      #pragma unroll
      for (int P = 1; P >= 0; P--) {
        const uint32_t base = stA + P * KV_PAIR;
        const int n = (1 - P) * 10;
        uint32_t a0, a1, a2, a3;
        norm2(n, a0, a1); norm2(n + 1, a2, a3);
        if (P == 0) named_sync(1, 256);
        stsm4(base, a0, a1, a2, a3);
        norm2(n + 2, a0, a1); norm2(n + 3, a2, a3);
        stsm4(base + 4096, a0, a1, a2, a3);
        norm2(n + 4, a0, a1); norm2(n + 5, a2, a3);
        stsm4(base + 8192, a0, a1, a2, a3);
        norm2(n + 6, a0, a1); norm2(n + 7, a2, a3);
        const uint32_t one_e = c4 == 2 ? 0x3F80u : 0u, one_o = c4 == 0 ? 0x3F80u : 0u;
        stsm4(base + 12288, a0, a1, c4 < 2 ? a2 : one_e, c4 < 2 ? a3 : one_e);
        norm2(n + 8, a0, a1);
        stsm4(base + 16384, c4 < 2 ? one_o : a2, c4 < 2 ? one_o : a3, a0, a1);
        norm2(n + 9, a0, a1);
        stsm2(base + 20480, a0, a1);
        fence_async();
        __syncwarp();
        if (lane == 0) mbar_arrive(bar(B_KVW + 1 - P));
      }
      #pragma unroll
      for (int i = 0; i < 10; i++) norm2(20 + i, qf[i][0], qf[i][1]);
      if (wg == 0) { asm volatile("bar.arrive 1, 256;" ::: "memory"); named_sync(2, 128); }
      else named_sync(1, 256);
    }
    uint32_t hr[10][2];
    {
      float A[32], B[32], Oe[12], Oo[12], Xe[12], Xo[12];
      uint32_t qe[6], qo[6], ye[6], yo[6];
      uint32_t sh[4] = {0u, 0u, 0u, 0u}, xh[4] = {0u, 0u, 0u, 0u};
      uint32_t z0, z1, z2, z3;
      const bool lowq = c4 < 2;
      {
        const uint32_t ml = lowq ? ~0u : 0u;
        qe[0] = qf[0][0]; qe[1] = qf[0][1]; qe[2] = qf[1][0]; qe[3] = qf[1][1]; qe[4] = qf[2][0] & ml; qe[5] = qf[2][1] & ml;
        qo[0] = qf[2][0] & ~ml; qo[1] = qf[2][1] & ~ml; qo[2] = qf[3][0]; qo[3] = qf[3][1]; qo[4] = qf[4][0]; qo[5] = qf[4][1];
        ye[0] = qf[5][0]; ye[1] = qf[5][1]; ye[2] = qf[6][0]; ye[3] = qf[6][1]; ye[4] = qf[7][0] & ml; ye[5] = qf[7][1] & ml;
        yo[0] = qf[7][0] & ~ml; yo[1] = qf[7][1] & ~ml; yo[2] = qf[8][0]; yo[3] = qf[8][1]; yo[4] = qf[9][0]; yo[5] = qf[9][1];
      }
      const int w = rbw & 3;
      const int b0 = 2 * c4 - 4;
      const uint32_t zown = lowq ? 0u : (b0 > w ? 0xF180u : 0u) | (b0 + 1 > w ? 0xF1800000u : 0u);
      const uint32_t zfar = lowq ? 0u : (b0 < w ? 0xF180u : 0u) | (b0 + 1 < w ? 0xF1800000u : 0u);
      const uint32_t zvoid = lowq ? 0u : 0xF180F180u;
      auto zmask = [&](uint32_t e) {
        const uint32_t lo = 0u - ((e >> 19) & 1u), hi = 0u - ((e >> 20) & 1u);
        return (zown & lo & ~hi) | (zfar & hi & ~lo) | (zvoid & lo & hi);
      };
      const uint32_t mk = (2 * c4 <= g ? 0xffffu : 0u) | (2 * c4 + 1 <= g ? 0xffff0000u : 0u);
      const uint32_t kq = SB0 >> 4, vlo = desc_lo(10240, 128), kcq = (SB0 + S_KC) >> 4;
      const uint32_t* sched = p.sched[rbA < 2 ? rbA : 2][wg];
      auto qk_even = [&](uint32_t t) {
        wgmma_rs_n64_t0(A, qe[0], qe[1], qe[2], qe[3], desc<128, 0>(t | (128u << 16), 0), 0);
        wgmma_rs_n64_t0(A, qe[4], qe[5], z0, z1, desc<128, 0>((t + 256) | ((kcq - 256 - t) << 16), 0), 1);
      };
      auto qk_odd = [&](uint32_t t) {
        wgmma_rs_n64_t0(B, qo[0], qo[1], z2, z3, desc<128, 0>((t + 256) | ((kcq - 256 - t) << 16), 0), 0);
        wgmma_rs_n64_t0(B, qo[2], qo[3], qo[4], qo[5], desc<128, 0>((t + 384) | (128u << 16), 0), 1);
      };
      auto swapr = [&](uint32_t& a, uint32_t& b) { asm volatile("{\n.reg .b32 t;\nmov.b32 t, %0;\nmov.b32 %0, %1;\nmov.b32 %1, t;\n}" : "+r"(a), "+r"(b)); };
      auto swapf = [&](float& a, float& b) { asm volatile("{\n.reg .f32 t;\nmov.f32 t, %0;\nmov.f32 %0, %1;\nmov.f32 %1, t;\n}" : "+f"(a), "+f"(b)); };
      auto swap_pair = [&]() {
        #pragma unroll
        for (int i = 0; i < 6; i++) { swapr(qe[i], ye[i]); swapr(qo[i], yo[i]); }
        #pragma unroll
        for (int i = 0; i < 4; i++) swapr(sh[i], xh[i]);
      };
      auto probs = [&](const float (&S)[32], uint32_t (&pf)[4][4], uint32_t m0, uint32_t m1, uint32_t m2) {
        #pragma unroll
        for (int b = 0; b < 4; b++) {
          #pragma unroll
          for (int i = 0; i < 4; i++) pf[b][i] = pack2(ex2(S[8 * b + 2 * i]), ex2(S[8 * b + 2 * i + 1]));
          if (b == w) { pf[b][0] &= m0; pf[b][1] &= m1; pf[b][2] &= m2; pf[b][3] &= m0; }
        }
      };
      bool shifted = false, early = false;
      while (true) {
        bool done = false;
        #pragma unroll
        for (int i = 0; i < 12; i++) asm volatile("mov.f32 %0, 0f00000000;\nmov.f32 %1, 0f00000000;\nmov.f32 %2, 0f00000000;\nmov.f32 %3, 0f00000000;" : "=f"(Oe[i]), "=f"(Oo[i]), "=f"(Xe[i]), "=f"(Xo[i]));
        uint32_t e0 = sched[0];
        int u = 0;
        #pragma unroll 1
        while (true) {
          { const uint32_t zm = zmask(e0); z0 = zm | sh[0]; z1 = zm | sh[1]; z2 = zm | sh[2]; z3 = zm | sh[3]; }
          wg_fence();
          qk_even(kq + (e0 & 0xffffu));
          wg_commit();
          wg_fence();
          qk_odd(kq + (e0 & 0xffffu));
          wg_commit();
          wg_wait<1>();
          #pragma unroll 1
          do {
            do {} while (0);
            const uint32_t e1 = sched[++u];
            const uint32_t kb = kq + (e1 & 0xffffu), vb = vlo + (e0 & 0xffffu), kvbar = bar(B_KVFULL + ((e1 >> 22) & 3));
            const uint32_t arrived = mbar_probe(kvbar, e1 & S_WAIT);
            const uint32_t t0 = e0 & S_MASK, f = t0 == S_FAR ? ~0u : 0u, any = (t0 == S_OWN || t0 == S_FAR) ? 0u : ~0u;
            const uint32_t m0 = (mk ^ f) | any, m1 = ~f | any, m2 = f | any, zm = zmask(e1);
            uint32_t pe[4][4], po[4][4];
            reg_fence(A);
            probs(A, pe, m0, m1, m2);
            wg_wait<0>();
            z0 = zm | sh[0]; z1 = zm | sh[1];
            mbar_wait_probed(kvbar, arrived, nspin);
            wg_fence();
            #pragma unroll
            for (int b = 0; b < 4; b++) wgmma_rs_n24_t1(Oe, pe[b][0], pe[b][1], pe[b][2], pe[b][3], desc<2048, 0>(vb, b * 256), 1);
            qk_even(kb);
            wg_commit();
            reg_fence(B);
            probs(B, po, m0, m1, m2);
            wg_wait<0>();
            z2 = zm | sh[2]; z3 = zm | sh[3];
            wg_fence();
            #pragma unroll
            for (int b = 0; b < 4; b++) wgmma_rs_n24_t1(Oo, po[b][0], po[b][1], po[b][2], po[b][3], desc<2048, 0>(vb, 6144 + b * 256), 1);
            qk_odd(kb);
            wg_commit();
            e0 = e1;
          } while (!(e0 & S_OSW));
          wg_wait<0>();
          reg_fence(Oe); reg_fence(Oo); reg_fence(A); reg_fence(B);
          if (!(e0 & S_CUR) && (!early || (e0 & S_END))) {
            const int se = (lane & 28) | 2, so = lane & 28;
            const float l0 = __shfl_sync(~0u, Oe[8], se), l1 = __shfl_sync(~0u, Oe[10], se), l2 = __shfl_sync(~0u, Oo[0], so), l3 = __shfl_sync(~0u, Oo[2], so);
            constexpr uint32_t LO = (127u - 60u) << 23, RANGE = 120u << 23;
            const uint32_t bad = (uint32_t)(__float_as_uint(l0) - LO > RANGE) | (uint32_t)(__float_as_uint(l1) - LO > RANGE) |
                                 (uint32_t)(__float_as_uint(l2) - LO > RANGE) | (uint32_t)(__float_as_uint(l3) - LO > RANGE);
            const bool last = e0 & S_END;
            bool good = shifted || !__any_sync(~0u, bad);
            if (last) {
              uint32_t redo;
              asm volatile("{\n.reg .pred p, q;\nsetp.ne.u32 q, %1, 0;\nbar.red.or.pred p, %2, 128, q;\nselp.u32 %0, 1, 0, p;\n}"
                           : "=r"(redo) : "r"((uint32_t)!(good && early)), "r"(2 + wg) : "memory");
              good = done = !__shfl_sync(~0u, redo, 0);
            }
            if (good) {
              uint8_t* og = reinterpret_cast<uint8_t*>(p.scr->o) + (rbA * 8 + hq) * OT_BYTES + (last ? 0 : OT_HALF) + (rbw * 16 + g) * 16 + c4 * 4;
              const float e0r = rcp(l0), e1r = rcp(l1), o0 = rcp(l2), o1 = rcp(l3);
              const float m0 = lowq ? e0r : o0, m1 = lowq ? e1r : o1;
              const float a = lowq ? Oe[8] : Oo[0], b = lowq ? Oe[9] : Oo[1], c = lowq ? Oe[10] : Oo[2], d = lowq ? Oe[11] : Oo[3];
              stg_u32(og, pack2(Oe[0] * e0r, Oe[1] * e0r)); stg_u32(og + 128, pack2(Oe[2] * e1r, Oe[3] * e1r));
              stg_u32(og + 2048, pack2(Oe[4] * e0r, Oe[5] * e0r)); stg_u32(og + 2176, pack2(Oe[6] * e1r, Oe[7] * e1r));
              stg_u32(og + 4096, pack2(a * m0, b * m0)); stg_u32(og + 4224, pack2(c * m1, d * m1));
              stg_u32(og + 6144, pack2(Oo[4] * o0, Oo[5] * o0)); stg_u32(og + 6272, pack2(Oo[6] * o1, Oo[7] * o1));
              stg_u32(og + 8192, pack2(Oo[8] * o0, Oo[9] * o0)); stg_u32(og + 8320, pack2(Oo[10] * o1, Oo[11] * o1));
            }
            if (!last && !shifted) {
              #pragma unroll
              for (int i = 0; i < 12; i++) { Oe[i] = Xe[i]; Oo[i] = Xo[i]; }
              mbar_wait(bar(B_XR), 0, nspin);
              const uint32_t row = warp * 16 + (lane & 7) + ((lane >> 3) & 1) * 8;
              const uint32_t xa = sb + XR_OFF + row * 128 + (((lane >> 4) ^ (row & 7)) << 4);
              #pragma unroll
              for (int i = 0; i < 5; i++) {
                uint32_t r[4];
                ldsm4(i < 4 ? xa ^ (i * 32) : sb + XR1_OFF + row * 32 + (lane >> 4) * 16, r);
                #pragma unroll
                for (int u = 0; u < 4; u++) (i < 3 ? Xe[4 * i + u] : Xo[4 * (i - 3) + u]) = __uint_as_float(r[u]);
              }
            }
            if (good) {
              __syncwarp();
              if (lane == 0) mbar_arrive(bar(last ? B_OW : B_OW + 1));
              early = true;
            }
          }
          if (e0 & S_END) break;
          swap_pair();
          if ((e0 & S_CUR) || shifted) {
            #pragma unroll
            for (int i = 0; i < 12; i++) { swapf(Oe[i], Xe[i]); swapf(Oo[i], Xo[i]); }
          }
        }
        if (done) break;
        shifted = true;
        z0 = z1 = z2 = z3 = 0u;
        #pragma unroll 1
        for (int P = 0; P < 2; P++) {
          float me0 = -INFINITY, me1 = -INFINITY, mo0 = -INFINITY, mo1 = -INFINITY;
          #pragma unroll 1
          for (int u = 0; u < 10; u++) {
            const uint32_t e = sched[u];
            if ((e & S_MASK) == S_MASK || ((e & S_CUR) != 0) != (P != 0)) continue;
            asm volatile("" : "+r"(z0), "+r"(z1), "+r"(z2), "+r"(z3));
            wg_fence();
            qk_even(kq + (e & 0xffffu));
            qk_odd(kq + (e & 0xffffu));
            wg_commit();
            wg_wait<0>();
            reg_fence(A); reg_fence(B);
            const bool msk = e & S_MASK, far = (e & S_MASK) == S_FAR;
            const int k0 = 2 * c4 <= g, k1 = 2 * c4 + 1 <= g;
            #pragma unroll
            for (int b = 0; b < 4; b++) {
              const bool pa = !msk || (w + k0 > b) != far, pb = !msk || (w + k1 > b) != far, pc = !msk || (w >= b) != far, pd = !msk || (w > b) != far;
              const float* a = &A[8 * b];
              const float* o = &B[8 * b];
              if (pa) { me0 = fmaxf(me0, a[0]); me1 = fmaxf(me1, a[6]); mo0 = fmaxf(mo0, o[0]); mo1 = fmaxf(mo1, o[6]); }
              if (pb) { me0 = fmaxf(me0, a[1]); me1 = fmaxf(me1, a[7]); mo0 = fmaxf(mo0, o[1]); mo1 = fmaxf(mo1, o[7]); }
              if (pc) { me1 = fmaxf(me1, fmaxf(a[2], a[3])); mo1 = fmaxf(mo1, fmaxf(o[2], o[3])); }
              if (pd) { me0 = fmaxf(me0, fmaxf(a[4], a[5])); mo0 = fmaxf(mo0, fmaxf(o[4], o[5])); }
            }
          }
          auto split = [&](float m) {
            m = -quad_max(m);
            const uint32_t h = pack2(m, 0.f) & 0xffffu;
            const float r = m - bf_lo(h);
            const uint32_t d = pack2(r, 0.f) & 0xffffu;
            return c4 == 0 ? h | (d << 16) : c4 == 1 ? pack2(r - bf_lo(d), 0.f) & 0xffffu : 0u;
          };
          sh[0] = split(me0); sh[1] = split(me1); sh[2] = split(mo0); sh[3] = split(mo1);
          swap_pair();
        }
      }
      #pragma unroll
      for (int i = 0; i < 20; i++) hr[i >> 1][i & 1] = __float_as_uint(i < 12 ? Xe[i] : Xo[i - 12]);
      if (shifted) {
        const __nv_bfloat16* xp = p.x + (size_t)(rbC * 128 + warp * 16 + g) * DM + 2 * c4;
        #pragma unroll
        for (int t = 0; t < 10; t++) {
          const __nv_bfloat16* q = xp + (t < 8 ? colM + 8 * t : colR + 8 * (t - 8));
          hr[t][0] = ldg_u32(q); hr[t][1] = ldg_u32(q + 8 * DM);
        }
      }
    }
    const int r0 = warp * 16 + g;
    const uint32_t stsm_row = (uint32_t)(warp * 16 + ((lane >> 3) & 1) * 8 + (lane & 7)) * 16 + (uint32_t)(lane >> 4) * 2048;
    {
      float acc[40];
      const uint32_t alo = desc_lo(wg * 1024, 2048), blo = desc_lo(0, 2560);
      mbar_wait(bar(B_WOFULL), 0, nspin);
      #pragma unroll 1
      for (int t = 0; t < 8; t++) {
        const int s = t & 3;
        mbar_wait(bar(B_CFULL + s), t >> 2, nspin);
        if (t >= 4) mbar_wait(bar(B_WOL + s), 0, nspin);
        const uint32_t a = alo + (ot_off(s) >> 4), b = blo + (((t < 4 ? WOE_OFF : WOL_OFF) + s * WO_BYTES) >> 4);
        wg_fence();
        #pragma unroll
        for (int ks = 0; ks < 5; ks++)
          wgmma_ss_n80_t1(acc, desc<128, 0>(a, ks * 4096), desc<256, 3>(b, ks * 512), (t > 0 || ks > 0) ? 1 : 0);
        wg_commit();
        if (t == 3) { wg_wait<0>(); release_pair(B_CEMPTY + 3); } else wg_wait<1>();
        if (t >= 1 && t < 4) release_pair(B_CEMPTY + t - 1);
      }
      wg_wait<0>();
      reg_fence(acc);
      release_pair(B_CDONE);
      float s0 = 0.f, q0 = 0.f, s1 = 0.f, q1 = 0.f;
      uint8_t* hg = reinterpret_cast<uint8_t*>(p.scr->h) + (rbC * 8 + j) * HT_BYTES + r0 * 16 + c4 * 4;
      #pragma unroll
      for (int i = 0; i < 5; i++) {
        #pragma unroll
        for (int u = 0; u < 2; u++) {
          const int t = 2 * i + u;
          hr[t][0] = pack2(acc[4 * t] + bf_lo(hr[t][0]), acc[4 * t + 1] + bf_hi(hr[t][0]));
          hr[t][1] = pack2(acc[4 * t + 2] + bf_lo(hr[t][1]), acc[4 * t + 3] + bf_hi(hr[t][1]));
          const float a = bf_lo(hr[t][0]), b = bf_hi(hr[t][0]), c = bf_lo(hr[t][1]), d = bf_hi(hr[t][1]);
          s0 += a + b; q0 = fmaf(a, a, fmaf(b, b, q0)); s1 += c + d; q1 = fmaf(c, c, fmaf(d, d, q1));
        }
        stg_u32(hg + i * 4096, hr[2 * i][0]); stg_u32(hg + i * 4096 + 128, hr[2 * i][1]);
        stg_u32(hg + i * 4096 + 2048, hr[2 * i + 1][0]); stg_u32(hg + i * 4096 + 2176, hr[2 * i + 1][1]);
        if (i == 1) {
          named_sync(1, 256);
          #pragma unroll
          for (int k = 0; k < 1; k++) stsm4(sb + k * 4096 + stsm_row, hr[2 * k][0], hr[2 * k][1], hr[2 * k + 1][0], hr[2 * k + 1][1]);
        }
        if (i >= 1) stsm4(sb + i * 4096 + stsm_row, hr[2 * i][0], hr[2 * i][1], hr[2 * i + 1][0], hr[2 * i + 1][1]);
      }
      s0 = quad_sum(s0); q0 = quad_sum(q0); s1 = quad_sum(s1); q1 = quad_sum(q1);
      if (c4 == 0) {
        uint8_t* sg = hg + 20480 - r0 * 8;
        stg_f2(sg, s0, q0); stg_f2(sg + 64, s1, q1);
        sts_f2(sb + 20480 + r0 * 8, s0, q0); sts_f2(sb + 20480 + (r0 + 8) * 8, s1, q1);
      }
      fence_async();
      __syncwarp();
      if (lane == 0) mbar_arrive(bar(B_HW));
    }
    uint32_t fr[12][4];
    uint32_t bb[10];
    #pragma unroll
    for (int t = 0; t < 10; t++) bb[t] = ldg_u32(p.b2 + 2 * c4 + (t < 8 ? colM + 8 * t : colR + 8 * (t - 8)));
    {
      float acc[96];
      float hs0 = 0.f, hq0 = 0.f, hs1 = 0.f, hq1 = 0.f;
      const uint32_t alo = desc_lo(wg * 1024, 2048), blo = desc_lo(0, 10240);
      #pragma unroll 1
      for (int t = 0; t < 8; t++) {
        const int s = t & 3;
        mbar_wait(bar(B_DBFULL + s), t >> 2, nspin);
        mbar_wait(bar(B_DAFULL + s), t >> 2, nspin);
        if (t == 1 && tid == 0) { mbar_arrive_cluster(bar(B_P1D), 0); mbar_arrive_cluster(bar(B_P1D), 1); }
        const uint32_t a = alo + s * (HT_BYTES >> 4), b = blo + (db_off(s) >> 4);
        wg_fence();
        #pragma unroll
        for (int ks = 0; ks < 5; ks++)
          wgmma_ss_n192_t1(acc, desc<128, 0>(a, ks * 4096), desc<1024, 1>(b, ks * 2048), (t > 0 || ks > 0) ? 1 : 0);
        wg_commit();
        const float2 u0 = lds_f2(sb + s * HT_BYTES + 20480 + r0 * 8), u1 = lds_f2(sb + s * HT_BYTES + 20480 + (r0 + 8) * 8);
        hs0 += u0.x; hq0 += u0.y; hs1 += u1.x; hq1 += u1.y;
        wg_wait<1>();
        if (t > 0) { release_pair(B_DAEMPTY + ((t - 1) & 3)); if ((tid & 127) == 0) mbar_arrive(bar(B_DBEMPTY + ((t - 1) & 3))); }
      }
      wg_wait<0>();
      reg_fence(acc);
      if ((tid & 127) == 0) mbar_arrive(bar(B_DBEMPTY + 3));
      release_pair(B_DDONE);
      const float mu0 = hs0 * (1.f / DM), mu1 = hs1 * (1.f / DM);
      const float rs0 = rsq(fmaxf(hq0 * (1.f / DM) - mu0 * mu0, 0.f) + 1e-5f), rs1 = rsq(fmaxf(hq1 * (1.f / DM) - mu1 * mu1, 0.f) + 1e-5f);
      const float mr0 = -mu0 * rs0, mr1 = -mu1 * rs1;
      mbar_wait(bar(B_CS2), 0, nspin);
      const uint32_t cba = sb + S_CS2 + c4 * 16;
      float4 cbn[2] = {lds_f4(cba), lds_f4(cba + 64)};
      #pragma unroll
      for (int i = 0; i < 12; i++) {
        uint32_t (&r)[4] = fr[i];
        const float4 cbc[2] = {cbn[0], cbn[1]};
        if (i < 11) { cbn[0] = lds_f4(cba + (2 * i + 2) * 64); cbn[1] = lds_f4(cba + (2 * i + 3) * 64); }
        #pragma unroll
        for (int u = 0; u < 2; u++) {
          const int t = 2 * i + u;
          const float4 cb = cbc[u];
          r[2 * u] = sq2(pack2_relu(fmaf(acc[4 * t], rs0, fmaf(cb.x, mr0, cb.y)), fmaf(acc[4 * t + 1], rs0, fmaf(cb.z, mr0, cb.w))));
          r[2 * u + 1] = sq2(pack2_relu(fmaf(acc[4 * t + 2], rs1, fmaf(cb.x, mr1, cb.y)), fmaf(acc[4 * t + 3], rs1, fmaf(cb.z, mr1, cb.w))));
        }
        if (i == 3) {
          named_sync(1, 256);
          #pragma unroll
          for (int k = 0; k < 3; k++) stsm4(sb + rank * 49152 + k * 4096 + stsm_row, fr[k][0], fr[k][1], fr[k][2], fr[k][3]);
        }
        if (i >= 3) stsm4(sb + rank * 49152 + i * 4096 + stsm_row, r[0], r[1], r[2], r[3]);
        if ((i & 3) == 3) {
          fence_async();
          __syncwarp();
          if (lane == 0) mbar_arrive(bar(i == 11 ? B_FW : B_KVW + (i >> 2)));
        }
      }
    }
    {
      float X[32], Y[32];
      uint32_t pf[12][4];
      const uint32_t blo = desc_lo(0, 8192);
      const uint32_t peer = (rank ^ 1) * 49152;
      auto release = [&](int s) { if ((tid & 127) == 0) mbar_arrive(bar(B_EBEMPTY + s)); };
      auto group = [&](float (&acc)[32], uint32_t (&a)[12][4], int i) {
        const int s = i < 5 ? i : i - 5;
        const bool fresh = i < 2 || (i > 3 && !(i & 1));
        mbar_wait(bar(B_EBFULL + s), i / 5, nspin);
        if (i != 2) wg_fence();
        #pragma unroll
        for (int c = 0; c < 3; c++) {
          if (i == 2) {
            mbar_wait(bar(B_FFULL + c), 0, nspin);
            #pragma unroll
            for (int ks = 0; ks < 4; ks++) ldsm4(sb + peer + (4 * c + ks) * 4096 + stsm_row, a[4 * c + ks]);
            wg_fence();
          }
          #pragma unroll
          for (int ks = 0; ks < 4; ks++) {
            const uint32_t (&f)[4] = a[4 * c + ks];
            wgmma_rs_n64_t1(acc, f[0], f[1], f[2], f[3], desc<1024, 1>(blo + (eb_off(s) >> 4), c * 8192 + ks * 2048), (!fresh || c > 0 || ks > 0) ? 1 : 0);
          }
        }
        wg_commit();
      };
      const uint32_t srow = sb + warp * 2048 + ((lane & 7) + ((lane >> 3) & 1) * 8) * 128 + (((lane >> 4) ^ (lane & 7)) << 4);
      auto stage = [&](const float (&acc)[32], int k) {
        const uint32_t off = k < 3 ? peer + k * 16384 : eb_off(k - 3);
        #pragma unroll
        for (int u = 0; u < 4; u++) {
          uint32_t r[4];
          #pragma unroll
          for (int h = 0; h < 2; h++) {
            const float* a = &acc[8 * u + 4 * h];
            if (k < 2) {
              const int t = k == 0 ? 2 * u + h : 8 + h;
              const bool own = k == 0 || u == jj;
              const uint32_t b = own ? bb[t] : 0u, h0 = own ? hr[t][0] : 0u, h1 = own ? hr[t][1] : 0u;
              r[2 * h] = pack2(a[0] + bf_lo(b) + bf_lo(h0), a[1] + bf_hi(b) + bf_hi(h0));
              r[2 * h + 1] = pack2(a[2] + bf_lo(b) + bf_lo(h1), a[3] + bf_hi(b) + bf_hi(h1));
            } else {
              r[2 * h] = pack2(a[0], a[1]);
              r[2 * h + 1] = pack2(a[2], a[3]);
            }
          }
          stsm4((srow ^ (u << 5)) + off, r[0], r[1], r[2], r[3]);
        }
        fence_async();
        __syncwarp();
        if (lane == 0) mbar_arrive(bar(B_ST + 2 * k + wg));
      };
      group(X, fr, 0);
      group(Y, fr, 1);
      wg_wait<1>(); release(0);
      group(X, pf, 2);
      __syncwarp();
      if (lane == 0) mbar_arrive(bar(B_PF));
      cluster_arrive();
      wg_wait<1>(); release(1);
      group(Y, pf, 3);
      wg_wait<1>(); release(2);
      reg_fence(X);
      mbar_wait(bar(B_PF), 0, nspin);
      stage(X, 0);
      group(X, fr, 4);
      wg_wait<1>(); release(3);
      reg_fence(Y);
      stage(Y, 1);
      group(X, pf, 5);
      wg_wait<1>(); release(4);
      group(Y, fr, 6);
      wg_wait<1>(); release(0);
      reg_fence(X);
      stage(X, 2);
      group(Y, pf, 7);
      wg_wait<1>(); release(1);
      group(X, fr, 8);
      wg_wait<1>();
      reg_fence(Y);
      mbar_wait(bar(B_EBEMPTY + 0), 1, nspin);
      stage(Y, 3);
      group(X, pf, 9);
      wg_wait<0>();
      reg_fence(X);
      mbar_wait(bar(B_EBEMPTY + 1), 1, nspin);
      stage(X, 4);
    }
  }
  __syncwarp();
  cluster_wait();
}

typedef CUresult (*EncodeTiledFn)(CUtensorMap*, CUtensorMapDataType, cuuint32_t, void*, const cuuint64_t*, const cuuint64_t*, const cuuint32_t*,
                                  const cuuint32_t*, CUtensorMapInterleave, CUtensorMapSwizzle, CUtensorMapL2promotion, CUtensorMapFloatOOBfill);

static bool encode_map(EncodeTiledFn fn, CUtensorMap* m, const void* ptr, int rank, const cuuint64_t* dims, const cuuint64_t* strides, const cuuint32_t* box,
                       CUtensorMapSwizzle sw) {
  const cuuint32_t es[3] = {1, 1, 1};
  return fn(m, CU_TENSOR_MAP_DATA_TYPE_BFLOAT16, rank, const_cast<void*>(ptr), dims, strides, box, es, CU_TENSOR_MAP_INTERLEAVE_NONE, sw,
            CU_TENSOR_MAP_L2_PROMOTION_L2_256B, CU_TENSOR_MAP_FLOAT_OOB_FILL_NONE) == CUDA_SUCCESS;
}

static void attention_schedule(Params& p) {
  for (int cls = 0; cls < 3; cls++)
    for (int wg = 0; wg < 2; wg++) {
      uint32_t* s = p.sched[cls][wg];
      int n = 0;
      auto add = [&](int P, int st, bool d, uint32_t fl) {
        const bool valid = st <= cls;
        uint32_t e = ((kv_off(P, valid ? st : 0) + (d ? wg : 1 - wg) * 1024) >> 4) | fl | (P ? S_CUR : 0u);
        e |= !valid ? S_MASK : !d || st == 1 ? 0u : st == 0 ? S_OWN : S_FAR;
        if (valid && st > 0 && d) e |= S_WAIT | ((uint32_t)((st - 1) + 2 * (1 - P)) << 22);
        s[n++] = e;
      };
      for (int P = 0; P < 2; P++) { add(P, 0, true, P ? S_OSW : 0u); if (wg == 1) add(P, 0, false, 0u); }
      for (int P = 1; P >= 0; P--) {
        add(P, 1, true, P ? 0u : S_OSW); add(P, 1, false, 0u); add(P, 2, true, 0u);
        if (wg == 0) add(P, 2, false, 0u);
      }
      s[n++] = (kv_off(0, 0) >> 4) | S_OSW | S_END;
      s[n++] = kv_off(0, 0) >> 4;
    }
}

}

extern "C" void kernel_launch(void* const* d_in, const int* in_sizes, int n_in, void* d_out, int out_size) {
  using namespace blk;
  (void)in_sizes; (void)n_in; (void)out_size;
  static EncodeTiledFn encode = nullptr;
  static void* scratch = nullptr;
  if (!encode) {
    cudaDriverEntryPointQueryResult st;
    void* fn = nullptr;
    if (cudaGetDriverEntryPoint("cuTensorMapEncodeTiled", &fn, cudaEnableDefault, &st) != cudaSuccess || !fn) return;
    encode = reinterpret_cast<EncodeTiledFn>(fn);
    cudaFuncSetAttribute(fused_block_kernel, cudaFuncAttributeMaxDynamicSharedMemorySize, SMEM_BYTES);
    cudaGetSymbolAddress(&scratch, g_scr);
  }
  Params p;
  p.x = static_cast<const __nv_bfloat16*>(d_in[0]); p.wqkv = static_cast<const __nv_bfloat16*>(d_in[1]); p.wo = static_cast<const __nv_bfloat16*>(d_in[2]);
  p.w1 = static_cast<const __nv_bfloat16*>(d_in[4]); p.b1 = static_cast<const __nv_bfloat16*>(d_in[5]);
  p.w2 = static_cast<const __nv_bfloat16*>(d_in[6]); p.b2 = static_cast<const __nv_bfloat16*>(d_in[7]); p.out = static_cast<__nv_bfloat16*>(d_out);
  p.scr = static_cast<Scratch*>(scratch);
  attention_schedule(p);
  CUtensorMap mX, mWq, mWr, mW1, mW1r, mW2, mOut, mXr;
  bool ok = true;
  { cuuint64_t d[2] = {DM, SEQ}, s[1] = {DM * 2}; cuuint32_t b[2] = {64, 128}, br[2] = {16, 128};
    ok &= encode_map(encode, &mX, p.x, 2, d, s, b, CU_TENSOR_MAP_SWIZZLE_128B); ok &= encode_map(encode, &mXr, p.x, 2, d, s, br, CU_TENSOR_MAP_SWIZZLE_NONE); }
  { cuuint64_t d[3] = {DM, DM, 3}, s[2] = {3 * DM * 2, DM * 2}; cuuint32_t b[3] = {64, 32, 3}; ok &= encode_map(encode, &mWq, p.wqkv, 3, d, s, b, CU_TENSOR_MAP_SWIZZLE_128B); }
  { cuuint64_t d[3] = {DM, DM, 3}, s[2] = {3 * DM * 2, DM * 2}; cuuint32_t b[3] = {16, 32, 3}; ok &= encode_map(encode, &mWr, p.wqkv, 3, d, s, b, CU_TENSOR_MAP_SWIZZLE_32B); }
  { cuuint64_t d[2] = {FF, DM}, s[1] = {FF * 2}; cuuint32_t b[2] = {64, 64}, br[2] = {64, 16};
    ok &= encode_map(encode, &mW1, p.w1, 2, d, s, b, CU_TENSOR_MAP_SWIZZLE_128B); ok &= encode_map(encode, &mW1r, p.w1, 2, d, s, br, CU_TENSOR_MAP_SWIZZLE_128B); }
  { cuuint64_t d[2] = {DM, FF}, s[1] = {DM * 2}; cuuint32_t b[2] = {64, 64}; ok &= encode_map(encode, &mW2, p.w2, 2, d, s, b, CU_TENSOR_MAP_SWIZZLE_128B); }
  { cuuint64_t d[2] = {DM, SEQ}, s[1] = {DM * 2}; cuuint32_t b[2] = {64, 64}; ok &= encode_map(encode, &mOut, p.out, 2, d, s, b, CU_TENSOR_MAP_SWIZZLE_128B); }
  if (!ok) return;
  cudaLaunchConfig_t cfg = {};
  cfg.gridDim = dim3(NCTA); cfg.blockDim = dim3(384); cfg.dynamicSmemBytes = SMEM_BYTES; cfg.stream = cudaStreamPerThread;
  cudaLaunchAttribute at[1];
  at[0].id = cudaLaunchAttributeClusterDimension; at[0].val.clusterDim.x = 2; at[0].val.clusterDim.y = 1; at[0].val.clusterDim.z = 1;
  cfg.attrs = at; cfg.numAttrs = 1;
  cudaLaunchKernelEx(&cfg, fused_block_kernel, mX, mWq, mWr, mW1, mW1r, mW2, mOut, mXr, p);
}
```
